```python
import torch

def _softmax(x, axis=-1):
    return torch.softmax(x, dim=axis)

def _gelu(x):
    return torch.nn.functional.gelu(x, approximate='tanh')

def _silu(x):
    return torch.nn.functional.silu(x)

def _sigmoid(x):
    return torch.sigmoid(x)

def _layernorm(x, axis=-1, eps=1e-05):
    m = x.mean(dim=axis, keepdim=True)
    v = x.var(dim=axis, keepdim=True, unbiased=False)
    return (x - m) / torch.sqrt(v + eps)

def _scatter_add(tgt, idx, src, axis=0):
    return tgt.clone().index_add_(axis, idx, src)

def _segment_sum(src, seg, n):
    out = torch.zeros((n,) + src.shape[1:], dtype=src.dtype)
    return out.index_add_(0, seg, src)

def _pad(x, pw):
    flat = tuple((v for pair in reversed(pw) for v in pair))
    return torch.nn.functional.pad(x, flat)
kernel_name = 'standalone__dilated_atrous__vision'

def setup_inputs():

    _w = lambda a: (lambda t: t.to(torch.bfloat16) if t.is_floating_point() else t)(torch.as_tensor(a))
    H = W = 512
    C = 96
    k = 3
    return {'x': _w((lambda *s: torch.randn(*s, dtype=torch.bfloat16) * 0.05)(1, H, W, C)), 'w': _w((lambda *s: torch.randn(*s, dtype=torch.bfloat16) * 0.05)(k, k, C, C) * (1.0 / (k * C ** 0.5)))}

def reference(x, w):
    B, H, W, C = x.shape
    k = 3
    rate = 2
    pad = (k - 1) * rate // 2
    xp = _pad(x, ((0, 0), (pad, pad), (pad, pad), (0, 0)))
    out = torch.zeros_like(x)
    for i in range(k):
        for j in range(k):
            tap = xp[:, i * rate:i * rate + H, j * rate:j * rate + W, :].clone()
            out = out + torch.einsum('bhwc,co->bhwo', tap, w[i, j])
    return out
```

```cpp
#include <cuda_runtime.h>
#include <cuda_bf16.h>
#include <cuda.h>
#include <stdint.h>

namespace {

constexpr int IMG_H = 512, IMG_W = 512, CH = 96;
constexpr int IN_SLAB = 72 * 32;
constexpr int IN_ROW = 3 * IN_SLAB;
constexpr int NSLOT = 4;
constexpr int W_K8 = 3 * 512;
constexpr int W_TAP = 6 * W_K8;
constexpr int W_COMP = 3 * W_TAP;
constexpr int W_BYTES = 4 * W_COMP;
constexpr int OUT_SLAB = 64 * 64;
constexpr int OUT_BYTES = 3 * OUT_SLAB;
constexpr int X_BYTES = 128 * 48 * 2;
constexpr int SEND1 = 4;
constexpr int NIT = 16;
constexpr int NUM_CTAS = 128;
constexpr int OFF_OUT = W_BYTES;
constexpr int OFF_X = OFF_OUT + 2 * OUT_BYTES;
constexpr int OFF_IN = OFF_X + 2 * X_BYTES;
constexpr int OFF_BAR = OFF_IN + 2 * NSLOT * IN_ROW;
constexpr int SMEM_BYTES = 1024 + OFF_BAR + 256;
static_assert(SMEM_BYTES <= 232448, "smem");
constexpr uint32_t ROW_DELAY = 1300;

__device__ __forceinline__ uint32_t smem_u32(const void* p) {
    return (uint32_t)__cvta_generic_to_shared(p);
}
__device__ __forceinline__ void mbar_init(uint32_t bar, uint32_t count) {
    asm volatile("mbarrier.init.shared::cta.b64 [%0], %1;" ::"r"(bar), "r"(count) : "memory");
}
__device__ __forceinline__ void mbar_expect_tx(uint32_t bar, uint32_t bytes) {
    asm volatile("mbarrier.arrive.expect_tx.shared::cta.b64 _, [%0], %1;" ::"r"(bar), "r"(bytes) : "memory");
}
__device__ __forceinline__ void mbar_arrive(uint32_t bar) {
    asm volatile("mbarrier.arrive.shared::cta.b64 _, [%0];" ::"r"(bar) : "memory");
}
__device__ __forceinline__ void mbar_arrive_warp(uint32_t bar) {
    __syncwarp();
    asm volatile("{\n\t.reg .pred p;\n\telect.sync _|p, 0xffffffff;\n\t@p mbarrier.arrive.shared::cta.b64 _, [%0];\n\t}" ::"r"(bar) : "memory");
}
__device__ __forceinline__ void mbar_arrive_remote(uint32_t rbar) {
    asm volatile("mbarrier.arrive.relaxed.cluster.shared::cluster.b64 _, [%0];" ::"r"(rbar) : "memory");
}
__device__ __forceinline__ void mbar_wait(uint32_t bar, uint32_t parity) {
    uint32_t done;
    for (;;) {
        asm volatile(
            "{\n\t.reg .pred p;\n\t"
            "mbarrier.try_wait.parity.shared::cta.b64 p, [%1], %2;\n\t"
            "selp.u32 %0, 1, 0, p;\n\t}"
            : "=r"(done) : "r"(bar), "r"(parity) : "memory");
        if (done) return;
    }
}
__device__ __forceinline__ uint32_t mapa(uint32_t addr, uint32_t rank) {
    uint32_t r;
    asm("mapa.shared::cluster.u32 %0, %1, %2;" : "=r"(r) : "r"(addr), "r"(rank));
    return r;
}
__device__ __forceinline__ void tma_load_5d(uint32_t dst, const CUtensorMap* map, uint32_t bar,
                                            int c0, int c1, int c2, int c3, int c4) {
    asm volatile(
        "cp.async.bulk.tensor.5d.shared::cluster.global.mbarrier::complete_tx::bytes "
        "[%0], [%1, {%3, %4, %5, %6, %7}], [%2];"
        ::"r"(dst), "l"((uint64_t)map), "r"(bar), "r"(c0), "r"(c1), "r"(c2), "r"(c3), "r"(c4) : "memory");
}
__device__ __forceinline__ void tma_store_5d(const CUtensorMap* map, uint32_t src, int c0, int c1, int c2, int c3,
                                             int c4) {
    asm volatile("cp.async.bulk.tensor.5d.global.shared::cta.bulk_group [%0, {%2, %3, %4, %5, %6}], [%1];"
                 ::"l"((uint64_t)map), "r"(src), "r"(c0), "r"(c1), "r"(c2), "r"(c3), "r"(c4) : "memory");
}
__device__ __forceinline__ void load_row(uint32_t dst, const CUtensorMap* xmap, uint32_t fb, int rank, int strip, int row) {
    mbar_expect_tx(fb, IN_ROW);
    for (int s = 0; s < 3; ++s)
        tma_load_5d(dst + s * IN_SLAB, xmap, fb, rank * 48 + s * 16, 0, strip * 16 - 1, 0, row);
}

__device__ __forceinline__ void wgmma_fence() { asm volatile("wgmma.fence.sync.aligned;" ::: "memory"); }
__device__ __forceinline__ void wgmma_commit() { asm volatile("wgmma.commit_group.sync.aligned;" ::: "memory"); }
template <int N>
__device__ __forceinline__ void wgmma_wait() { asm volatile("wgmma.wait_group.sync.aligned %0;" ::"n"(N) : "memory"); }

__device__ __forceinline__ void wgmma_m64n96k16(float (&d)[48], const uint32_t* a, uint64_t db, int scale_d) {
    asm volatile(
        "{\n\t.reg .pred p;\n\t"
        "setp.ne.b32 p, %53, 0;\n\t"
        "wgmma.mma_async.sync.aligned.m64n96k16.f32.bf16.bf16 "
        "{%0, %1, %2, %3, %4, %5, %6, %7, %8, %9, %10, %11, %12, %13, %14, %15, "
        " %16, %17, %18, %19, %20, %21, %22, %23, %24, %25, %26, %27, %28, %29, %30, %31, "
        " %32, %33, %34, %35, %36, %37, %38, %39, %40, %41, %42, %43, %44, %45, %46, %47}, "
        "{%48, %49, %50, %51}, %52, p, 1, 1, 1;\n\t}"
        : "+f"(d[0]), "+f"(d[1]), "+f"(d[2]), "+f"(d[3]), "+f"(d[4]), "+f"(d[5]), "+f"(d[6]), "+f"(d[7]),
          "+f"(d[8]), "+f"(d[9]), "+f"(d[10]), "+f"(d[11]), "+f"(d[12]), "+f"(d[13]), "+f"(d[14]), "+f"(d[15]),
          "+f"(d[16]), "+f"(d[17]), "+f"(d[18]), "+f"(d[19]), "+f"(d[20]), "+f"(d[21]), "+f"(d[22]), "+f"(d[23]),
          "+f"(d[24]), "+f"(d[25]), "+f"(d[26]), "+f"(d[27]), "+f"(d[28]), "+f"(d[29]), "+f"(d[30]), "+f"(d[31]),
          "+f"(d[32]), "+f"(d[33]), "+f"(d[34]), "+f"(d[35]), "+f"(d[36]), "+f"(d[37]), "+f"(d[38]), "+f"(d[39]),
          "+f"(d[40]), "+f"(d[41]), "+f"(d[42]), "+f"(d[43]), "+f"(d[44]), "+f"(d[45]), "+f"(d[46]), "+f"(d[47])
        : "r"(a[0]), "r"(a[1]), "r"(a[2]), "r"(a[3]), "l"(db), "r"(scale_d));
}

template <int N>
__device__ __forceinline__ void fence_regs(float (&r)[N]) {
#pragma unroll
    for (int i = 0; i < N; ++i) asm volatile("" : "+f"(r[i])::"memory");
}

__device__ __forceinline__ uint32_t bf2_add(uint32_t a, uint32_t b) {
    uint32_t r;
    asm volatile("add.rn.bf16x2 %0, %1, %2;" : "=r"(r) : "r"(a), "r"(b));
    return r;
}
__device__ __forceinline__ uint32_t bf2_sub(uint32_t a, uint32_t b) {
    uint32_t r;
    asm volatile("sub.rn.bf16x2 %0, %1, %2;" : "=r"(r) : "r"(a), "r"(b));
    return r;
}
__device__ __forceinline__ uint32_t pack_bf16(float a, float b) {
    __nv_bfloat162 v = __floats2bfloat162_rn(a, b);
    return *reinterpret_cast<uint32_t*>(&v);
}

template <bool ADD>
__device__ __forceinline__ void make_quads(uint32_t (&q)[12], const uint32_t (&a)[24], const uint32_t (&b)[24], int kc) {
#pragma unroll
    for (int j = 0; j < 3; ++j) {
#pragma unroll
        for (int hl = 0; hl < 2; ++hl) {
#pragma unroll
            for (int h = 0; h < 2; ++h) {
                const int i = kc * 8 + (j + h) * 2 + hl;
                q[j * 4 + hl * 2 + h] = ADD ? bf2_add(a[i], b[i]) : bf2_sub(a[i], b[i]);
            }
        }
    }
}

struct Ctx {
    uint32_t full0, empty0, in0;
    uint32_t wdesc, wdesc0, wdesc3;
    uint32_t wready, wg;
    uint32_t ld_off0, ld_off1;
    uint32_t xfull, xfree, xbuf;
    uint32_t r_xfull, r_xbuf;
    uint32_t sfull, st_off;
};

__device__ __forceinline__ void ld_chunk(uint32_t (&r)[24], const Ctx& c, uint32_t slot_addr, int kc) {
    asm volatile("ldmatrix.sync.aligned.m8n8.x4.shared.b16 {%0, %1, %2, %3}, [%4];"
                 : "=r"(r[kc * 8 + 0]), "=r"(r[kc * 8 + 1]), "=r"(r[kc * 8 + 2]), "=r"(r[kc * 8 + 3])
                 : "r"(slot_addr + c.ld_off0 + kc * IN_SLAB) : "memory");
    asm volatile("ldmatrix.sync.aligned.m8n8.x4.shared.b16 {%0, %1, %2, %3}, [%4];"
                 : "=r"(r[kc * 8 + 4]), "=r"(r[kc * 8 + 5]), "=r"(r[kc * 8 + 6]), "=r"(r[kc * 8 + 7])
                 : "r"(slot_addr + c.ld_off1 + kc * IN_SLAB) : "memory");
}

__device__ __forceinline__ void mma3(float (&acc)[48], const uint32_t (&q)[12], const Ctx& c, int k, int kc,
                                     bool fresh) {
    uint32_t wd;
    asm volatile("mov.b32 %0, %1;" : "=r"(wd) : "r"(k == 0 ? c.wdesc0 : k == 3 ? c.wdesc3 : c.wdesc));
    wgmma_fence();
#pragma unroll
    for (int j = 0; j < 3; ++j) {
        const int m = k == 1 ? 1 : k == 2 ? 3 : 0;
        const uint32_t lo = wd + (uint32_t)((m * W_COMP + j * W_TAP + kc * 2 * W_K8) >> 4);
        const uint32_t hi = (uint32_t)(W_K8 >> 4) | (2u << 30);
        uint64_t db;
        asm("mov.b64 %0, {%1, %2};" : "=l"(db) : "r"(lo), "r"(hi));
        wgmma_m64n96k16(acc, &q[j * 4], db, (fresh && j == 0) ? 0 : 1);
    }
    wgmma_commit();
}

__device__ __forceinline__ void release_slot(const Ctx& c, int slot) {
    mbar_arrive_warp(c.empty0 + slot * 8);
}

template <int I0, int I1>
__device__ __forceinline__ void send_acc(float (&acc)[48], const Ctx& c, uint32_t par) {
    fence_regs(acc);
    if (I0 == 0) mbar_wait(c.xfree, par ^ 1);
    uint32_t rx;
    asm volatile("add.u32 %0, %1, %2;" : "=r"(rx) : "r"(c.xbuf), "r"(c.r_xbuf));
#pragma unroll
    for (int i = I0; i < I1; ++i) {
        uint32_t r0 = pack_bf16(acc[i * 8 + 0], acc[i * 8 + 1]);
        uint32_t r1 = pack_bf16(acc[i * 8 + 2], acc[i * 8 + 3]);
        uint32_t r2 = pack_bf16(acc[i * 8 + 4], acc[i * 8 + 5]);
        uint32_t r3 = pack_bf16(acc[i * 8 + 6], acc[i * 8 + 7]);
        asm volatile("st.async.weak.shared::cluster.mbarrier::complete_tx::bytes.v4.b32 [%0], {%1, %2, %3, %4}, [%5];"
                     ::"r"(rx + i * 2048), "r"(r0), "r"(r1), "r"(r2), "r"(r3), "r"(c.r_xfull) : "memory");
    }
}

__device__ __forceinline__ void fin_pack(float (&acc)[48], uint32_t (&pk)[24]) {
    fence_regs(acc);
#pragma unroll
    for (int i = 0; i < 24; ++i) {
        pk[i] = pack_bf16(acc[i * 2 + 0], acc[i * 2 + 1]);
        asm volatile("" : "+r"(pk[i]));
    }
}
__device__ __forceinline__ void finish_row(const uint32_t (&pk)[24], const Ctx& c, uint32_t par) {
    uint32_t v[24];
    mbar_wait(c.xfull, par);
#pragma unroll
    for (int i = 0; i < 6; ++i)
        asm volatile("ld.shared.v4.b32 {%0, %1, %2, %3}, [%4];"
                     : "=r"(v[i * 4 + 0]), "=r"(v[i * 4 + 1]), "=r"(v[i * 4 + 2]), "=r"(v[i * 4 + 3])
                     : "r"(c.xbuf + i * 2048) : "memory");
#pragma unroll
    for (int i = 0; i < 6; ++i) {
        uint32_t addr = (c.st_off ^ ((i & 1) * 32)) + (i >> 1) * OUT_SLAB;
        uint32_t r0 = bf2_add(pk[i * 4 + 0], v[i * 4 + 0]);
        uint32_t r1 = bf2_add(pk[i * 4 + 1], v[i * 4 + 1]);
        uint32_t r2 = bf2_add(pk[i * 4 + 2], v[i * 4 + 2]);
        uint32_t r3 = bf2_add(pk[i * 4 + 3], v[i * 4 + 3]);
        asm volatile("stmatrix.sync.aligned.m8n8.x4.shared.b16 [%0], {%1, %2, %3, %4};"
                     ::"r"(addr), "r"(r0), "r"(r1), "r"(r2), "r"(r3) : "memory");
    }
    mbar_arrive_warp(c.sfull);
}

template <int RANK>
__device__ __forceinline__ void butterfly(float (&s)[48], float (&k)[48]) {
    fence_regs(s);
    fence_regs(k);
#pragma unroll
    for (int i = 0; i < 48; ++i) {
        s[i] = (RANK == 0) ? __fsub_rn(s[i], k[i]) : __fadd_rn(s[i], k[i]);
        k[i] = __fmaf_rn(k[i], (RANK == 0) ? 2.f : -2.f, s[i]);
    }
}

__device__ __forceinline__ void stagger_lead(const Ctx& c, uint32_t id) {
    asm volatile("{\n\t.reg .pred p;\n\tsetp.eq.u32 p, %1, 0;\n\t@p bar.arrive %0, 256;\n\t}" ::"r"(id), "r"(c.wg) : "memory");
}
__device__ __forceinline__ void stagger_lag(const Ctx& c, uint32_t id) {
    asm volatile("{\n\t.reg .pred p;\n\tsetp.ne.u32 p, %1, 0;\n\t@p bar.sync %0, 256;\n\t}" ::"r"(id), "r"(c.wg) : "memory");
}
template <int SYNC>
__device__ __forceinline__ void catch_up(const Ctx& c, uint32_t k) {
    if (SYNC) asm volatile("{\n\t.reg .pred p;\n\tsetp.eq.u32 p, %0, 0;\n\t@p bar.sync 15, 256;\n\t}" ::"r"(k + c.wg) : "memory");
    else asm volatile("{\n\t.reg .pred p;\n\tsetp.eq.u32 p, %0, 0;\n\t@p bar.arrive 15, 256;\n\t}" ::"r"(k + (c.wg ^ 1)) : "memory");
}

template <int RANK>
__device__ __forceinline__ void p2_head(const Ctx& c, int slot, uint32_t ph, uint32_t (&qa)[12], const uint32_t (&d0)[24],
                                        const uint32_t (&d1)[24], const uint32_t (&d2)[24], uint32_t (&d3)[24]) {
    if (RANK == 0) {
        mbar_wait(c.full0 + slot * 8, ph);
        ld_chunk(d3, c, c.in0 + slot * IN_ROW, 0);
        ld_chunk(d3, c, c.in0 + slot * IN_ROW, 1);
        make_quads<false>(qa, d3, d1, 0);
    } else {
        make_quads<false>(qa, d0, d2, 0);
    }
}

template <int RANK, int PAR>
__device__ __forceinline__ void phase2(uint32_t k, const Ctx& c, float (&accS)[48], float (&accK)[48],
                                         uint32_t (&d0)[24], uint32_t (&d1)[24], uint32_t (&d2)[24],
                                         uint32_t (&d3)[24], uint32_t (&qa)[12], uint32_t (&qb)[12]) {
    constexpr uint32_t par = PAR;
    constexpr int slot3 = (2 * PAR + 3) & 3;
    const uint32_t ph = (k + 1) & 1;
    const uint32_t s3 = c.in0 + slot3 * IN_ROW;
    butterfly<RANK>(accS, accK);
    if (RANK == 0) {
        mma3(accS, qa, c, 3, 0, false);
        make_quads<false>(qb, d3, d1, 1);
        mma3(accS, qb, c, 3, 1, false);
        ld_chunk(d3, c, s3, 2);
        wgmma_wait<1>();
        make_quads<false>(qa, d3, d1, 2);
        if (PAR == 1) catch_up<1>(c, k);
        mma3(accS, qa, c, 3, 2, false);
        release_slot(c, slot3);
        wgmma_wait<1>();
        make_quads<false>(qb, d0, d2, 0);
        mma3(accK, qb, c, 0, 0, false);
        wgmma_wait<1>();
        make_quads<false>(qa, d0, d2, 1);
        mma3(accK, qa, c, 0, 1, false);
        send_acc<0, SEND1>(accS, c, par);
        wgmma_wait<1>();
        make_quads<false>(qb, d0, d2, 2);
        mma3(accK, qb, c, 0, 2, false);
    } else {
        mma3(accS, qa, c, 0, 0, false);
        make_quads<false>(qb, d0, d2, 1);
        mma3(accS, qb, c, 0, 1, false);
        mbar_wait(c.full0 + slot3 * 8, ph ^ PAR ^ 1);
        ld_chunk(d3, c, s3, 0);
        wgmma_wait<1>();
        make_quads<false>(qa, d0, d2, 2);
        if (PAR == 1) catch_up<1>(c, k);
        mma3(accS, qa, c, 0, 2, false);
        ld_chunk(d3, c, s3, 1);
        wgmma_wait<1>();
        make_quads<false>(qb, d3, d1, 0);
        mma3(accK, qb, c, 3, 0, false);
        ld_chunk(d3, c, s3, 2);
        wgmma_wait<1>();
        make_quads<false>(qa, d3, d1, 1);
        mma3(accK, qa, c, 3, 1, false);
        send_acc<0, SEND1>(accS, c, par);
        wgmma_wait<1>();
        make_quads<false>(qb, d3, d1, 2);
        mma3(accK, qb, c, 3, 2, false);
        release_slot(c, slot3);
    }
    mbar_wait(c.full0 + 2 * PAR * 8, ph);
#pragma unroll
    for (int kc = 0; kc < 3; ++kc) ld_chunk(d0, c, c.in0 + 2 * PAR * IN_ROW, kc);
    send_acc<SEND1, 6>(accS, c, par);
}
template <int RANK, int PAR>
__device__ __forceinline__ void phase1(uint32_t k, const Ctx& c, float (&accS)[48], float (&accK)[48],
                                       uint32_t (&d0)[24], uint32_t (&d1)[24], uint32_t (&d2)[24],
                                       uint32_t (&d3)[24], uint32_t (&qa)[12], uint32_t (&qb)[12]) {
    constexpr uint32_t par = PAR;
    constexpr int slot4 = 2 * PAR;
    const uint32_t ph = (k + 1) & 1;
    {
        wgmma_wait<1>();
        make_quads<true>(qa, d3, d0, 0);
        mma3(accS, qa, c, 1, 0, true);
        wgmma_wait<1>();
        make_quads<true>(qb, d3, d0, 1);
        mma3(accS, qb, c, 1, 1, false);
        uint32_t pk[24];
        fin_pack(accK, pk);
        const uint32_t id = 2 * k + PAR;
        wgmma_wait<1>();
        make_quads<true>(qa, d3, d0, 2);
        mma3(accS, qa, c, 1, 2, false);
        release_slot(c, slot4);
        finish_row(pk, c, par);
        wgmma_wait<1>();
        make_quads<false>(qb, d0, d3, 0);
        stagger_lag(c, id);
        mma3(accK, qb, c, 2, 0, true);
        wgmma_wait<1>();
        make_quads<false>(qa, d0, d3, 1);
        mma3(accK, qa, c, 2, 1, false);
        wgmma_wait<1>();
        make_quads<false>(qb, d0, d3, 2);
        mma3(accK, qb, c, 2, 2, false);
        stagger_lead(c, id);
        if (PAR == 0) catch_up<0>(c, k);
        wgmma_wait<1>();
        p2_head<RANK>(c, slot4 + 1, ph, qa, d2, d3, d0, d1);
    }
}

template <int RANK>
__device__ __forceinline__ void consumer(const Ctx& c) {
    float accS[48], accK[48];
    uint32_t d0[24], d1[24], d2[24], d3[24];
    uint32_t qa[12], qb[12];
#pragma unroll
    for (int i = 0; i < 48; ++i) { accS[i] = 0.f; accK[i] = 0.f; }
    mbar_wait(c.full0 + 8, 0);
#pragma unroll
    for (int kc = 0; kc < 3; ++kc) ld_chunk(d1, c, c.in0 + IN_ROW, kc);
    mbar_wait(c.full0 + 16, 0);
#pragma unroll
    for (int kc = 0; kc < 3; ++kc) ld_chunk(d2, c, c.in0 + 2 * IN_ROW, kc);
    make_quads<true>(qa, d1, d2, 0);
    mbar_wait(c.wready, 0);
    mma3(accS, qa, c, 1, 0, true);
    make_quads<false>(qb, d2, d1, 0);
    mma3(accK, qb, c, 2, 0, true);
    wgmma_wait<1>();
    make_quads<true>(qa, d1, d2, 1);
    mma3(accS, qa, c, 1, 1, false);
    wgmma_wait<1>();
    make_quads<false>(qb, d2, d1, 1);
    mma3(accK, qb, c, 2, 1, false);
    wgmma_wait<1>();
    make_quads<true>(qa, d1, d2, 2);
    release_slot(c, 1);
    release_slot(c, 2);
    mma3(accS, qa, c, 1, 2, false);
    wgmma_wait<1>();
    make_quads<false>(qb, d2, d1, 2);
    mma3(accK, qb, c, 2, 2, false);
    mbar_wait(c.full0, 0);
#pragma unroll
    for (int kc = 0; kc < 3; ++kc) ld_chunk(d0, c, c.in0, kc);
    {
        uint32_t x = d0[0] | d0[4] | d0[8] | d0[12] | d0[16] | d0[20];
        asm volatile("{\n\t.reg .pred p;\n\tsetp.eq.u32 p, %0, 0x7fc17fc1;\n\t@p nanosleep.u32 0;\n\t}" ::"r"(x) : "memory");
    }
    release_slot(c, 0);
    wgmma_wait<1>();
    p2_head<RANK>(c, 3, 0, qa, d0, d1, d2, d3);
    wgmma_wait<0>();
#pragma unroll 1
    for (uint32_t k = 0; k < NIT / 2; ++k) {
        phase2<RANK, 0>(k, c, accS, accK, d0, d1, d2, d3, qa, qb);
        phase1<RANK, 0>(k, c, accS, accK, d0, d1, d2, d3, qa, qb);
        wgmma_wait<0>();
        phase2<RANK, 1>(k, c, accS, accK, d2, d3, d0, d1, qa, qb);
        if (__builtin_expect(k == NIT / 2 - 1, 0)) {
            asm volatile("wgmma.wait_group.sync.aligned 0; // last" ::: "memory");
            uint32_t pk[24];
            fin_pack(accK, pk);
            finish_row(pk, c, 1);
            return;
        }
        phase1<RANK, 1>(k, c, accS, accK, d2, d3, d0, d1, qa, qb);
        wgmma_wait<0>();
    }
    uint32_t pk[24];
    fin_pack(accK, pk);
    finish_row(pk, c, 1);
}

__device__ __forceinline__ void wt_load(uint32_t (&g)[36], uint32_t unit, int lane) {
    const uint32_t src = unit + (lane >> 2) * 192 + (((lane ^ (lane >> 3)) & 3) << 4);
#pragma unroll
    for (int i = 0; i < 9; ++i)
        asm volatile("ld.shared.v4.b32 {%0, %1, %2, %3}, [%4];"
                     : "=r"(g[i * 4]), "=r"(g[i * 4 + 1]), "=r"(g[i * 4 + 2]), "=r"(g[i * 4 + 3])
                     : "r"(src + (i / 3) * 64 + (i % 3) * W_COMP) : "memory");
}
__device__ __forceinline__ void sts128(uint32_t addr, const uint32_t* v) {
    asm volatile("st.shared.v4.b32 [%0], {%1, %2, %3, %4};" ::"r"(addr), "r"(v[0]), "r"(v[1]), "r"(v[2]), "r"(v[3]) : "memory");
}
__device__ __forceinline__ void wt_store(const uint32_t (&g)[36], uint32_t unit, int lane) {
    const uint32_t dst = unit + lane * 16;
    __syncwarp();
#pragma unroll
    for (int r = 0; r < 3; ++r) {
        const uint32_t *a = &g[r * 12], *b = a + 4, *cc = a + 8;
        sts128(dst + r * 512, a);
        sts128(dst + r * 512 + 2 * W_COMP, cc);
        uint32_t u1[4], u2[4];
#pragma unroll
        for (int i = 0; i < 4; ++i) {
            uint32_t h;
            asm("add.rn.bf16x2 %0, %1, %2;" : "=r"(h) : "r"(a[i]), "r"(cc[i]));
            asm("mul.rn.bf16x2 %0, %1, %2;" : "=r"(h) : "r"(h), "r"(0x3f003f00u));
            asm("fma.rn.bf16x2 %0, %1, %2, %3;" : "=r"(u1[i]) : "r"(b[i]), "r"(0x3f003f00u), "r"(h));
            asm("fma.rn.bf16x2 %0, %1, %2, %3;" : "=r"(u2[i]) : "r"(b[i]), "r"(0xbf00bf00u), "r"(h));
        }
        sts128(dst + r * 512 + W_COMP, u1);
        sts128(dst + r * 512 + 3 * W_COMP, u2);
    }
}

__device__ __forceinline__ int seq_row(int seg, int row_par, int n) {
    const int q = (seg & 1) ? seg * 2 * NIT - 1 + n : seg * 2 * NIT + 2 * NIT - n;
    return 2 * q + row_par;
}

__global__ void __cluster_dims__(2, 1, 1) __launch_bounds__(384, 1)
conv_kernel(const __grid_constant__ CUtensorMap xmap, const __grid_constant__ CUtensorMap omap,
            const char* __restrict__ wp) {
    extern __shared__ uint8_t smem_raw[];
    const uint32_t base = (smem_u32(smem_raw) + 1023u) & ~1023u;
    const uint32_t wbase = base;
    const uint32_t bar_base = base + OFF_BAR;
    const uint32_t full_b = bar_base, empty_b = bar_base + 64, wbar_b = bar_base + 128;
    const uint32_t xfull_b = bar_base + 152, xfree_b = bar_base + 168, sfull_b = bar_base + 184, wready_b = bar_base + 200;

    const int tid = threadIdx.x;
    const int warp = tid >> 5, lane = tid & 31;
    const int rank = blockIdx.x & 1;
    const int cluster = blockIdx.x >> 1;
    const int strip = cluster & 7, seg = cluster >> 3;
    uint32_t c_start;
    asm volatile("mov.u32 %0, %clock;" : "=r"(c_start) :: "memory");

    if (warp == 3) {
        if (lane < 20) {
            const char* p = wp + (size_t)(((blockIdx.x & 63) * 20 + lane + (blockIdx.x >> 6) * 16) * 128);
            asm volatile("prefetch.global.L2 [%0];" ::"l"(p) : "memory");
        }
        if (lane == 0) asm volatile("prefetch.tensormap [%0];" ::"l"((uint64_t)&xmap) : "memory");
    }
    if (tid == 0) {
        for (int i = 0; i < 3; ++i) mbar_init(wbar_b + i * 8, 1);
        asm volatile("fence.mbarrier_init.release.cluster;" ::: "memory");
        asm volatile("fence.proxy.async.shared::cta;" ::: "memory");
    }
    if (tid == 32) {
        for (int i = 0; i < 4; ++i) mbar_init(full_b + (i >> 1) * 32 + 8 + (i & 1) * 8, 1);
        asm volatile("fence.mbarrier_init.release.cluster;" ::: "memory");
        asm volatile("fence.proxy.async.shared::cta;" ::: "memory");
    }
    if (tid == 64) {
        for (int i = 0; i < 4; ++i) mbar_init(full_b + (i >> 1) * 32 + (i & 1) * 24, 1);
        for (int i = 0; i < 8; ++i) mbar_init(empty_b + i * 8, 4);
        for (int i = 0; i < 4; ++i) mbar_init(xfull_b + i * 8, 1);
        for (int i = 0; i < 2; ++i) mbar_init(sfull_b + i * 8, 4);
        mbar_init(wready_b, 8);
        mbar_expect_tx(xfull_b, X_BYTES);
        mbar_expect_tx(xfull_b + 8, X_BYTES);
        asm volatile("fence.mbarrier_init.release.cluster;" ::: "memory");
        asm volatile("fence.proxy.async.shared::cta;" ::: "memory");
    }
    __syncwarp();
    asm volatile("barrier.cluster.arrive.relaxed.aligned;" ::: "memory");
    if (tid == 0) {
#pragma unroll 1
        for (int j = 0; j < 3; ++j) {
            mbar_expect_tx(wbar_b + j * 8, 3 * W_TAP);
#pragma unroll
            for (int i = 0; i < 3; ++i)
                asm volatile("cp.async.bulk.shared::cluster.global.mbarrier::complete_tx::bytes [%0], [%1], %2, [%3];"
                             ::"r"(wbase + (i * 3 + j) * W_TAP), "l"(wp + (2 * (i * 3 + j) + rank) * W_TAP), "r"(W_TAP),
                               "r"(wbar_b + j * 8) : "memory");
        }
    }
    if (tid == 32) {
#pragma unroll 1
        for (int i = 0; i < 4; ++i) {
            const int slot = (i >> 1) * NSLOT + 1 + (i & 1);
            while ((uint32_t)clock() - c_start < ROW_DELAY) {}
            load_row(base + OFF_IN + slot * IN_ROW, &xmap, full_b + slot * 8, rank, strip, seq_row(seg, i >> 1, 1 + (i & 1)));
        }
    }
    __syncwarp();

    if (warp >= 8) {
        asm volatile("setmaxnreg.dec.sync.aligned.u32 24;");
        asm volatile("barrier.cluster.wait.aligned;" ::: "memory");
        if (lane == 0) {
            const int wg = warp & 1;
            if (warp < 10) {
                mbar_wait(full_b + 16, 0);
#pragma unroll 1
                for (int i = 2; i < 2 * NIT + 2; ++i) {
                    const int n = i == 2 ? 0 : i;
                    const int slot = wg * NSLOT + (n & 3);
                    if (n >= NSLOT) mbar_wait(empty_b + slot * 8, ((n >> 2) & 1) ^ 1);
                    load_row(base + OFF_IN + slot * IN_ROW, &xmap, full_b + slot * 8, rank, strip, seq_row(seg, wg, n));
                }
                mbar_wait(empty_b + (wg * NSLOT + 2) * 8, 1);
                mbar_arrive(full_b + (wg * NSLOT + 2) * 8);
            } else {
                const uint32_t src = base + OFF_OUT + wg * OUT_BYTES;
                const uint32_t r_xfree = mapa(xfree_b + wg * 8, rank ^ 1);
#pragma unroll 1
                for (int t = 0; t < NIT; ++t) {
                    mbar_wait(sfull_b + wg * 8, t & 1);
                    if (t + 1 < NIT) mbar_arrive_remote(r_xfree);
                    asm volatile("fence.proxy.async.shared::cta;" ::: "memory");
                    const int orow = seq_row(seg, wg, 2 * t + 1 + rank);
                    for (int s = 0; s < 3; ++s) tma_store_5d(&omap, src + s * OUT_SLAB, s * 32, 0, strip * 16, 0, orow);
                    asm volatile("cp.async.bulk.commit_group;" ::: "memory");
                    asm volatile("cp.async.bulk.wait_group.read 0;" ::: "memory");
                    if (t + 1 < NIT) mbar_expect_tx(xfull_b + wg * 8, X_BYTES);
                }
            }
        }
    } else {
        asm volatile("setmaxnreg.inc.sync.aligned.u32 240;");
        asm volatile("barrier.cluster.wait.aligned;" ::: "memory");
        const int uwarp = __shfl_sync(0xffffffffu, warp, 0);
        const int wg = uwarp >> 2;
        const int w4 = warp & 3;
        const int t128 = tid & 127;
        {
            uint32_t ga[36], gb[36];
            const uint32_t unit = wbase + uwarp * W_K8;
            mbar_wait(wbar_b + (uwarp < 6 ? 0 : 8), 0);
            wt_load(ga, unit, lane);
            mbar_wait(wbar_b + (uwarp < 4 ? 8 : 16), 0);
            wt_load(gb, unit + 8 * W_K8, lane);
            wt_store(ga, unit, lane);
            if (uwarp < 2) {
                mbar_wait(wbar_b + 16, 0);
                wt_load(ga, unit + 16 * W_K8, lane);
            }
            wt_store(gb, unit + 8 * W_K8, lane);
            if (uwarp < 2) wt_store(ga, unit + 16 * W_K8, lane);
            asm volatile("fence.proxy.async.shared::cta;" ::: "memory");
            mbar_arrive_warp(wready_b);
        }
        Ctx c;
        c.full0 = full_b + wg * NSLOT * 8;
        c.empty0 = empty_b + wg * NSLOT * 8;
        c.in0 = base + OFF_IN + wg * NSLOT * IN_ROW;
        c.wdesc = ((wbase & 0x3FFFF) >> 4) | ((uint32_t)(512 >> 4) << 16);
        const int up = (seg & 1) ^ 1;
        c.wdesc0 = c.wdesc + up * (2 * W_COMP >> 4);
        c.wdesc3 = c.wdesc + (1 - up) * (2 * W_COMP >> 4);
        c.wready = wready_b;
        c.wg = wg;
        {
            const int m = lane >> 3, gg = lane & 7, hl = m & 1;
            const int s0 = m >> 1;
            const int rho0 = (s0 == 0) ? (36 + 8 * w4 + gg) : (8 * w4 + gg + 2);
            const int rho1 = rho0 + 2;
            c.ld_off0 = rho0 * 32 + ((hl ^ ((rho0 >> 2) & 1)) << 4);
            c.ld_off1 = rho1 * 32 + ((hl ^ ((rho1 >> 2) & 1)) << 4);
            const int rho = ((lane >> 3) & 1) * 32 + 8 * w4 + gg;
            c.st_off = base + OFF_OUT + wg * OUT_BYTES + rho * 64 + ((((lane >> 4) ^ (rho >> 1)) & 3) << 4);
        }
        c.xfull = xfull_b + wg * 8;
        c.xfree = xfree_b + wg * 8;
        c.xbuf = base + OFF_X + wg * X_BYTES + t128 * 16;
        c.r_xfull = mapa(c.xfull, rank ^ 1);
        c.r_xbuf = c.r_xfull - c.xfull;
        c.sfull = sfull_b + wg * 8;
        c.ld_off0 = __shfl_sync(0xffffffffu, c.ld_off0, lane);
        c.ld_off1 = __shfl_sync(0xffffffffu, c.ld_off1, lane);
        c.st_off = __shfl_sync(0xffffffffu, c.st_off, lane);
        c.xbuf = __shfl_sync(0xffffffffu, c.xbuf, lane);
        if (rank == 0) consumer<0>(c);
        else consumer<1>(c);
    }
}

typedef CUresult (*EncodeFn)(CUtensorMap*, CUtensorMapDataType, cuuint32_t, void*, const cuuint64_t*,
                             const cuuint64_t*, const cuuint32_t*, const cuuint32_t*, CUtensorMapInterleave,
                             CUtensorMapSwizzle, CUtensorMapL2promotion, CUtensorMapFloatOOBfill);

}

extern "C" void kernel_launch(void* const* d_in, const int* in_sizes, int n_in, void* d_out, int out_size) {
    (void)in_sizes; (void)n_in; (void)out_size;
    static EncodeFn encode = nullptr;
    if (!encode) {
        void* fn = nullptr;
        cudaDriverEntryPointQueryResult qres;
        cudaGetDriverEntryPoint("cuTensorMapEncodeTiled", &fn, cudaEnableDefault, &qres);
        encode = (EncodeFn)fn;
        cudaFuncSetAttribute(conv_kernel, cudaFuncAttributeMaxDynamicSharedMemorySize, SMEM_BYTES);
    }
    CUtensorMap xmap, omap;
    cuuint64_t dims5[5] = {(cuuint64_t)CH, 2, (cuuint64_t)IMG_W / 4, 2, (cuuint64_t)IMG_H};
    cuuint64_t strides5[4] = {(cuuint64_t)CH * 2, (cuuint64_t)CH * 2 * 4, (cuuint64_t)CH * 2 * 2,
                              (cuuint64_t)IMG_W * CH * 2};
    cuuint32_t estr5[5] = {1, 1, 1, 1, 1};
    {
        cuuint32_t box[5] = {16, 2, 18, 2, 1};
        encode(&xmap, CU_TENSOR_MAP_DATA_TYPE_BFLOAT16, 5, d_in[0], dims5, strides5, box, estr5,
               CU_TENSOR_MAP_INTERLEAVE_NONE, CU_TENSOR_MAP_SWIZZLE_32B, CU_TENSOR_MAP_L2_PROMOTION_L2_128B,
               CU_TENSOR_MAP_FLOAT_OOB_FILL_NONE);
    }
    {
        cuuint32_t box[5] = {32, 2, 16, 2, 1};
        encode(&omap, CU_TENSOR_MAP_DATA_TYPE_BFLOAT16, 5, d_out, dims5, strides5, box, estr5,
               CU_TENSOR_MAP_INTERLEAVE_NONE, CU_TENSOR_MAP_SWIZZLE_64B, CU_TENSOR_MAP_L2_PROMOTION_NONE,
               CU_TENSOR_MAP_FLOAT_OOB_FILL_NONE);
    }
    conv_kernel<<<NUM_CTAS, 384, SMEM_BYTES>>>(xmap, omap, (const char*)d_in[1]);
}
```

```cpp
#include <cuda_runtime.h>
#include <cuda_bf16.h>
#include <cuda.h>
#include <stdint.h>

namespace {

#define ST_EF
#define PF 7
#define PF0 5
#define EQ0 0x7fe
#define EQ1 0x7fe
#define PLA0 0xf0122334455fff45ull
#define PLA1 0xff012334455fff45ull
#define PLB0 0x444455899a000000ull
#define PLB1 PLB0
#define FMODE0 1
#define FMODE1 1
#define ORD 0
#define FMODE (RANK == 0 ? FMODE0 : FMODE1)
#define LT0 0x10
#define LT1 LT0
#define LATE(n) (((RANK == 0 ? LT0 : LT1) >> (n)) & 1)
#define LL0 0x30
#define LL1 LL0
#define LLATE(n) (((RANK == 0 ? LL0 : LL1) >> (n)) & 1)
#define PO0 0x012654
#define PO1 PO0
#define PG(g) (((RANK == 0 ? PO0 : PO1) >> (20 - (g) * 4)) & 7)
#define M1FIRST (PG(2) >= 4 ? PG(2) & 3 : PG(3) & 3)
#define EBSLOT (PG(2) == 2 ? 8 : PG(3) == 2 ? 9 : 10)
#define NW0 0
#define NW1 NW0
#define NW(n) (((RANK == 0 ? NW0 : NW1) >> (n)) & 1)
#define DEC 1
#define RORD 0x675231
#define PW0 0
#define PW1 1
#define EPO 0x8c04ab9231ull
#define PROMO CU_TENSOR_MAP_L2_PROMOTION_L2_128B
#define ZEND 1
#define HPIN 0
#define LL2 0x20
#define LLATE2(n) ((LL2 >> (n)) & 1)
#define CPT 0x01234
#define CP(k) ((CPT >> (16 - 4 * (k))) & 7)
#define MEF 0
#define DEFW 0
#define PKSLOT 7
#define EQ(n) (((RANK == 0 ? EQ0 : EQ1) >> (n)) & 1)
#define LAGPOS 9
#define SEND1 4
#define SEND2 6
#define TL(slot)
#define TLC(slot)
constexpr int IMG_H = 512, IMG_W = 512, CH = 96;
constexpr int IN_SLAB = 72 * 32;
constexpr int IN_ROW = 3 * IN_SLAB;
constexpr int SL0 = 0, SL4 = IN_SLAB, SL2 = 2 * IN_SLAB, SL3 = 3 * IN_SLAB, IN_B = 8 * IN_SLAB;
constexpr int W_K8 = 3 * 512;
constexpr int W_TAP = 6 * W_K8;
constexpr int W_COMP = 3 * W_TAP;
constexpr int W_BYTES = 5 * W_COMP;
constexpr int X_CH = 32 * 64;
constexpr int X_UNIT = 3 * X_CH;
constexpr int X_BYTES = 3 * X_UNIT;
constexpr int X_TX = X_UNIT;
constexpr int SEG = 32;
constexpr int NIT = 11;
constexpr int NUM_CTAS = 128;
#define LAY 3
constexpr int OFF_W = LAY == 0 ? 0 : LAY == 1 ? 2 * X_BYTES : LAY == 2 ? 2 * X_BYTES + 8 * IN_ROW : 8 * IN_ROW;
constexpr int OFF_X = LAY == 0 ? W_BYTES : LAY == 3 ? W_BYTES + 8 * IN_ROW : 0;
constexpr int OFF_IN = LAY == 3 ? 0 : LAY == 2 ? 2 * X_BYTES : W_BYTES + 2 * X_BYTES;
constexpr int OFF_BAR = W_BYTES + 2 * X_BYTES + 8 * IN_ROW;
constexpr int SMEM_BYTES = 1024 + OFF_BAR + 1024;
static_assert(SMEM_BYTES <= 232448, "smem");
#define RDEL 1100
constexpr uint32_t ROW_DELAY = RDEL;
constexpr int B_FULL0 = 0, B_FULLA = 8, B_FULLB = 16, B_FULLC = 24, B_EMPTYE = 32, B_EMPTYF = 40, B_EMPTYB = 48, B_HFULL = 56,
              B_FFULL = 64, B_SH = 72, B_SF = 80;

__device__ __forceinline__ uint32_t smem_u32(const void* p) {
    return (uint32_t)__cvta_generic_to_shared(p);
}
__device__ __forceinline__ void mbar_init(uint32_t bar, uint32_t count) {
    asm volatile("mbarrier.init.shared::cta.b64 [%0], %1;" ::"r"(bar), "r"(count) : "memory");
}
__device__ __forceinline__ void mbar_expect_tx(uint32_t bar, uint32_t bytes) {
    asm volatile("mbarrier.arrive.expect_tx.shared::cta.b64 _, [%0], %1;" ::"r"(bar), "r"(bytes) : "memory");
}
__device__ __forceinline__ void mbar_arrive(uint32_t bar) {
    asm volatile("mbarrier.arrive.shared::cta.b64 _, [%0];" ::"r"(bar) : "memory");
}
__device__ __forceinline__ void mbar_arrive_warp(uint32_t bar) {
    __syncwarp();
    asm volatile("{\n\t.reg .pred p;\n\telect.sync _|p, 0xffffffff;\n\t@p mbarrier.arrive.shared::cta.b64 _, [%0];\n\t}" ::"r"(bar) : "memory");
}
__device__ __forceinline__ void mbar_arrive_remote(uint32_t rbar) {
    asm volatile("mbarrier.arrive.relaxed.cluster.shared::cluster.b64 _, [%0];" ::"r"(rbar) : "memory");
}
__device__ __forceinline__ void mbar_expect_tx_remote(uint32_t rbar, uint32_t bytes) {
    asm volatile("mbarrier.arrive.expect_tx.relaxed.cluster.shared::cluster.b64 _, [%0], %1;" ::"r"(rbar), "r"(bytes) : "memory");
}
__device__ __forceinline__ void mbar_wait(uint32_t bar, uint32_t parity) {
    uint32_t done;
    for (;;) {
        asm volatile(
            "{\n\t.reg .pred p;\n\t"
            "mbarrier.try_wait.parity.shared::cta.b64 p, [%1], %2;\n\t"
            "selp.u32 %0, 1, 0, p;\n\t}"
            : "=r"(done) : "r"(bar), "r"(parity) : "memory");
        if (done) return;
    }
}
__device__ __forceinline__ uint32_t mapa(uint32_t addr, uint32_t rank) {
    uint32_t r;
    asm("mapa.shared::cluster.u32 %0, %1, %2;" : "=r"(r) : "r"(addr), "r"(rank));
    return r;
}
__device__ __forceinline__ void tma_load_5d(uint32_t dst, const CUtensorMap* map, uint32_t bar,
                                            int c0, int c1, int c2, int c3, int c4, bool keep) {
    asm volatile(
        "cp.async.bulk.tensor.5d.shared::cluster.global.mbarrier::complete_tx::bytes "
        "[%0], [%1, {%3, %4, %5, %6, %7}], [%2];"
        ::"r"(dst), "l"((uint64_t)map), "r"(bar), "r"(c0), "r"(c1), "r"(c2), "r"(c3), "r"(c4) : "memory");
}
__device__ __forceinline__ void tma_store_4d(const CUtensorMap* map, uint32_t src, int c0, int c1, int c2, int c3) {
    uint64_t pol;
    asm volatile("createpolicy.fractional.L2::evict_first.b64 %0, 1.0;" : "=l"(pol));
    asm volatile("cp.async.bulk.tensor.5d.global.shared::cta.bulk_group.L2::cache_hint [%0, {%2, %2, %3, %2, %4}], [%1], %5;"
                 ::"l"((uint64_t)map), "r"(src), "r"(c0), "r"(c3 * 128 + c1), "r"(c2), "l"(pol) : "memory");
}
__device__ __forceinline__ void load_row(uint32_t dst, uint32_t dstb, const CUtensorMap* xmap, uint32_t fb, int rank, int strip, int row, bool keep) {
    tma_load_5d(dst, xmap + 1, fb, rank * 64, 0, strip * 16 - 1, 0, row, keep);
    tma_load_5d(dstb, xmap, fb, 32 + rank * 16, 0, strip * 16 - 1, 0, row, keep);
}

__device__ __forceinline__ void wgmma_fence() { asm volatile("wgmma.fence.sync.aligned;" ::: "memory"); }
__device__ __forceinline__ void wgmma_commit() { asm volatile("wgmma.commit_group.sync.aligned;" ::: "memory"); }
template <int N>
__device__ __forceinline__ void wgmma_wait() { asm volatile("wgmma.wait_group.sync.aligned %0;" ::"n"(N) : "memory"); }

__device__ __forceinline__ void wgmma_m64n96k16(float (&d)[48], const uint32_t* a, uint64_t db, int scale_d) {
    asm volatile(
        "{\n\t.reg .pred p;\n\t"
        "setp.ne.b32 p, %53, 0;\n\t"
        "wgmma.mma_async.sync.aligned.m64n96k16.f32.bf16.bf16 "
        "{%0, %1, %2, %3, %4, %5, %6, %7, %8, %9, %10, %11, %12, %13, %14, %15, "
        " %16, %17, %18, %19, %20, %21, %22, %23, %24, %25, %26, %27, %28, %29, %30, %31, "
        " %32, %33, %34, %35, %36, %37, %38, %39, %40, %41, %42, %43, %44, %45, %46, %47}, "
        "{%48, %49, %50, %51}, %52, p, 1, 1, 1;\n\t}"
        : "+f"(d[0]), "+f"(d[1]), "+f"(d[2]), "+f"(d[3]), "+f"(d[4]), "+f"(d[5]), "+f"(d[6]), "+f"(d[7]),
          "+f"(d[8]), "+f"(d[9]), "+f"(d[10]), "+f"(d[11]), "+f"(d[12]), "+f"(d[13]), "+f"(d[14]), "+f"(d[15]),
          "+f"(d[16]), "+f"(d[17]), "+f"(d[18]), "+f"(d[19]), "+f"(d[20]), "+f"(d[21]), "+f"(d[22]), "+f"(d[23]),
          "+f"(d[24]), "+f"(d[25]), "+f"(d[26]), "+f"(d[27]), "+f"(d[28]), "+f"(d[29]), "+f"(d[30]), "+f"(d[31]),
          "+f"(d[32]), "+f"(d[33]), "+f"(d[34]), "+f"(d[35]), "+f"(d[36]), "+f"(d[37]), "+f"(d[38]), "+f"(d[39]),
          "+f"(d[40]), "+f"(d[41]), "+f"(d[42]), "+f"(d[43]), "+f"(d[44]), "+f"(d[45]), "+f"(d[46]), "+f"(d[47])
        : "r"(a[0]), "r"(a[1]), "r"(a[2]), "r"(a[3]), "l"(db), "r"(scale_d));
}

template <int N>
__device__ __forceinline__ void fence_regs(float (&r)[N]) {
#pragma unroll
    for (int i = 0; i < N; ++i) asm volatile("" : "+f"(r[i])::"memory");
}

__device__ __forceinline__ uint32_t bf2_add(uint32_t a, uint32_t b) {
    uint32_t r;
    asm volatile("add.rn.bf16x2 %0, %1, %2;" : "=r"(r) : "r"(a), "r"(b));
    return r;
}
__device__ __forceinline__ uint32_t bf2_sub(uint32_t a, uint32_t b) {
    uint32_t r;
    asm volatile("sub.rn.bf16x2 %0, %1, %2;" : "=r"(r) : "r"(a), "r"(b));
    return r;
}
template <uint32_t B>
__device__ __forceinline__ uint32_t bf2_fma(uint32_t a, uint32_t cc) {
    uint32_t r;
    asm volatile("fma.rn.bf16x2 %0, %1, %2, %3;" : "=r"(r) : "r"(a), "r"(B), "r"(cc));
    return r;
}
__device__ __forceinline__ uint32_t pack_bf16(float a, float b) {
    __nv_bfloat162 v = __floats2bfloat162_rn(a, b);
    return *reinterpret_cast<uint32_t*>(&v);
}

__device__ __forceinline__ uint32_t opaque_add(uint32_t a, uint32_t b) {
    uint32_t r;
    asm volatile("add.u32 %0, %1, %2;" : "=r"(r) : "r"(a), "r"(b));
    return r;
}
template <int K>
__device__ __forceinline__ void make_quads(uint32_t (&q)[12], const uint32_t (&x)[24], const uint32_t (&d2)[24],
                                           const uint32_t (&u)[24], int kc, uint32_t coef = 0) {
    uint32_t e[8];
#pragma unroll
    for (int i = 0; i < 8; ++i) e[i] = K == 1 ? bf2_add(x[kc * 8 + i], d2[kc * 8 + i]) : bf2_sub(x[kc * 8 + i], d2[kc * 8 + i]);
#pragma unroll
    for (int jj = 0; jj < 3; ++jj) {
        const int j = jj == 0 ? 1 : jj == 1 ? 0 : 2;
#pragma unroll
        for (int hl = 0; hl < 2; ++hl) {
#pragma unroll
            for (int h = 0; h < 2; ++h) {
                const int i = ((j + h) >> 1) * 4 + hl * 2 + ((j + h) & 1);
                const uint32_t uu = u[kc * 8 + i];
                if (K < 0) asm volatile("fma.rn.bf16x2 %0, %1, %2, %3;" : "=r"(q[j * 4 + hl * 2 + h]) : "r"(uu), "r"(coef), "r"(e[i]));
                else q[j * 4 + hl * 2 + h] = K == 0 ? bf2_fma<0x3f003f00u>(uu, e[i]) : K == 1 ? bf2_sub(e[i], uu)
                                      : K == 2 ? bf2_fma<0x40404040u>(e[i], uu) : bf2_fma<0xc000c000u>(uu, e[i]);
            }
        }
    }
}
template <bool MAKE_U>
__device__ __forceinline__ void make_mid(uint32_t (&q)[12], uint32_t (&d1)[24], const uint32_t (&d2)[24], uint32_t (&u)[24], int kc,
                                         const uint32_t (&d3)[24]) {
    uint32_t y[8];
#pragma unroll
    for (int i = 0; i < 8; ++i) {
        y[i] = bf2_sub(d2[kc * 8 + i], d3[kc * 8 + i]);
        if (MAKE_U) asm volatile("sub.rn.bf16x2 %0, %0, %1;" : "+r"(u[kc * 8 + i]) : "r"(d1[kc * 8 + i]));
        asm volatile("fma.rn.bf16x2 %0, %0, %2, %1;" : "+r"(d1[kc * 8 + i]) : "r"(y[i]), "r"(0x40004000u));
    }
#pragma unroll
    for (int jj = 0; jj < 3; ++jj) {
        const int j = jj == 0 ? 1 : jj == 1 ? 0 : 2;
#pragma unroll
        for (int hl = 0; hl < 2; ++hl) {
#pragma unroll
            for (int h = 0; h < 2; ++h) {
                const int i = ((j + h) >> 1) * 4 + hl * 2 + ((j + h) & 1);
                q[j * 4 + hl * 2 + h] = bf2_fma<0x3fc03fc0u>(y[i], u[kc * 8 + i]);
            }
        }
    }
}

struct Ctx {
    uint32_t bar;
    uint32_t wdesc;
    uint32_t wready, wg, tlo, k, zero, tlo2, vz, ua;
    int rk;
    uint32_t ld0, ld1;
    uint32_t xbuf;
    uint32_t r_off;
};

__device__ __forceinline__ void sb(const Ctx& c) {
    asm volatile("{\n\t.reg .pred q;\n\tsetp.eq.u32 q, %1, 7;\n\t@q mov.u32 %0, %clock;\n\t}" : "+r"(const_cast<Ctx&>(c).vz) : "r"(c.wg) : "memory");
}
__device__ __forceinline__ void sbz(const Ctx& c) {
    asm volatile("{\n\t.reg .pred q;\n\tsetp.eq.u32 q, %1, 7;\n\t@q mov.u32 %0, %clock;\n\t}" : "+r"(const_cast<Ctx&>(c).zero) : "r"(c.wg) : "memory");
}
#define FTW(n)
#define FTM
__device__ __forceinline__ void sbk(Ctx& c) {
    asm volatile("{\n\t.reg .pred q;\n\tsetp.eq.u32 q, %1, 7;\n\t@q mov.u32 %0, %clock;\n\t}" : "+r"(c.k) : "r"(c.wg) : "memory");
}
template <int OFF>
__device__ __forceinline__ void ldsm(uint32_t* r, uint32_t a, uint32_t ua) {
    asm volatile("{\n\t.reg .u32 t;\n\tadd.u32 t, %4, %5;\n\tldmatrix.sync.aligned.m8n8.x4.shared.b16 {%0, %1, %2, %3}, [t + %6];\n\t}"
                 : "=r"(r[0]), "=r"(r[1]), "=r"(r[2]), "=r"(r[3]) : "r"(a), "r"(ua), "n"(OFF) : "memory");
}
template <bool PLUS>
__device__ __forceinline__ uint32_t addr2(uint32_t b, uint32_t t) {
    uint32_t r;
    if (PLUS) asm volatile("mad.lo.s32 %0, %1, 2, %2;" : "=r"(r) : "r"(b), "r"(t));
    else asm volatile("{\n\t.reg .s32 x;\n\tneg.s32 x, %2;\n\tmad.lo.s32 %0, %1, 2, x;\n\t}" : "=r"(r) : "r"(b), "r"(t));
    return r;
}
template <int SLOT, int KC>
__device__ __forceinline__ void ld_chunk_t(uint32_t (&r)[24], const Ctx& c, uint32_t ua, uint32_t ub) {
    if (KC == 2) {
        ldsm<SLOT>(&r[16], c.ld0, ub);
        ldsm<SLOT>(&r[20], c.ld1, ub);
    } else {
        ldsm<2 * SLOT + KC * 16>(&r[KC * 8], addr2<KC == 0>(c.ld0, c.vz), ua);
        ldsm<2 * SLOT + 16 - KC * 16>(&r[KC * 8 + 4], addr2<KC != 0>(c.ld1, c.vz), ua);
    }
}
#define ld_chunk(r, c, slot, kc) ld_chunk_t<slot, kc>(r, c, c.ua, 0)

__device__ __forceinline__ void mma3p(float (&acc)[48], const uint32_t* q0, const uint32_t* q1, const uint32_t* q2,
                                      const Ctx& c, int k, int kc, bool fresh) {
    uint32_t wd;
    asm volatile("mov.b32 %0, %1;" : "=r"(wd) : "r"(c.wdesc));
    wgmma_fence();
#pragma unroll
    for (int j = 0; j < 3; ++j) {
        const uint32_t lo = wd + (uint32_t)((CP(k) * W_COMP + j * W_TAP + (kc == 2 ? 4 - 4 * c.rk : kc + 2 * c.rk) * W_K8) >> 4);
        const uint32_t hi = (uint32_t)((kc == 2 ? W_K8 : 2 * W_K8) >> 4) | (2u << 30);
        uint64_t db;
        asm("mov.b64 %0, {%1, %2};" : "=l"(db) : "r"(lo), "r"(hi));
        wgmma_m64n96k16(acc, j == 0 ? q0 : j == 1 ? q1 : q2, db, (fresh && j == 0) ? 0 : 1);
    }
    wgmma_commit();
}
__device__ __forceinline__ void mma3(float (&acc)[48], const uint32_t (&q)[12], const Ctx& c, int k, int kc, bool fresh) {
    mma3p(acc, &q[0], &q[4], &q[8], c, k, kc, fresh);
}
__device__ __forceinline__ void make_dup(uint32_t (&q)[12], const uint32_t (&u)[24], const Ctx& c, int kc) {
#pragma unroll
    for (int i = 0; i < 4; ++i)
        q[kc * 4 + i] = opaque_add(u[kc * 8 + (i & 1) * 3 + (i >> 1) * 2 + 1], c.zero);
}
__device__ __forceinline__ void mma3d(float (&acc)[48], const uint32_t (&u)[24], const uint32_t (&q)[12], const Ctx& c, int k, int kc, int first = 0) {
    mma3p(acc, &u[kc * 8], &q[kc * 4], &u[kc * 8 + 4], c, k, kc, kc == first);
}
__device__ __forceinline__ void mma3u(float (&acc)[48], const uint32_t (&u)[24], uint32_t (&q)[12], const Ctx& c, int kc) {
    make_dup(q, u, c, kc);
    mma3d(acc, u, q, c, 3, kc);
}

__device__ __forceinline__ uint32_t pack_word(const float (&acc)[48], int i, int m) {
    const int o = ((i % 3) * 4 + m) * 4 + (i / 3) * 2;
    return pack_bf16(acc[o], acc[o + 1]);
}
__device__ __forceinline__ void st_async(uint32_t addr, uint32_t r0, uint32_t r1, uint32_t r2, uint32_t r3, uint32_t rbar) {
    asm volatile("st.async.weak.shared::cluster.mbarrier::complete_tx::bytes.v4.b32 [%0], {%1, %2, %3, %4}, [%5];"
                 ::"r"(addr), "r"(r0), "r"(r1), "r"(r2), "r"(r3), "r"(rbar) : "memory");
}
template <int I0, int I1, int SUB>
__device__ __forceinline__ void send_acc(float (&acc)[48], const Ctx& c, int n = 0) {
    if (I0 >= I1) return;
    fence_regs(acc);
    const uint32_t ro = c.r_off + (c.zero >> n), rx = c.xbuf + ro, rb = c.bar + B_FFULL + ro;
#pragma unroll
    for (int i = I0; i < I1; ++i)
        st_async(rx + ((i - SUB) / 3) * X_UNIT + (i % 3) * X_CH, pack_word(acc, i, 0), pack_word(acc, i, 1), pack_word(acc, i, 2),
                 pack_word(acc, i, 3), rb);
}
template <int I, bool H = true>
__device__ __forceinline__ void send_half(const uint32_t (&p)[12], const Ctx& c, int n = 0) {
    const uint32_t ro = c.r_off + (c.zero >> n), rx = c.xbuf + ro, rb = c.bar + (H ? B_HFULL : B_FFULL) + ro;
    st_async(rx + (H ? 2 * X_UNIT : 0) + I * X_CH, p[I * 4], p[I * 4 + 1], p[I * 4 + 2], p[I * 4 + 3], rb);
}
template <int I0, int N>
__device__ __forceinline__ void fin_pack(float (&acc)[48], uint32_t (&pk)[N * 4]) {
    fence_regs(acc);
#pragma unroll
    for (int i = 0; i < N * 4; ++i) {
        pk[i] = pack_word(acc, I0 + (i >> 2), i & 3);
        asm volatile("" : "+r"(pk[i]));
    }
}
template <int N>
__device__ __forceinline__ void fin_load(uint32_t (&v)[N * 4], const Ctx& c, int off) {
#pragma unroll
    for (int i = 0; i < N; ++i)
        asm volatile("ld.shared.v4.b32 {%0, %1, %2, %3}, [%4];"
                     : "=r"(v[i * 4 + 0]), "=r"(v[i * 4 + 1]), "=r"(v[i * 4 + 2]), "=r"(v[i * 4 + 3])
                     : "r"(c.xbuf + off + (i / 3) * X_UNIT + (i % 3) * X_CH) : "memory");
}
template <int N>
__device__ __forceinline__ void fin_store(uint32_t (&pk)[N * 4], const uint32_t (&v)[N * 4], const Ctx& c, int off, int sbar) {
#pragma unroll
    for (int i = 0; i < N; ++i) {
#pragma unroll
        for (int j = i * 4; j < i * 4 + 4; ++j) asm volatile("add.rn.bf16x2 %0, %0, %1;" : "+r"(pk[j]) : "r"(v[j]));
        asm volatile("st.shared.v4.b32 [%0], {%1, %2, %3, %4};"
                     ::"r"(c.xbuf + off + (i / 3) * X_UNIT + (i % 3) * X_CH), "r"(pk[i * 4]), "r"(pk[i * 4 + 1]), "r"(pk[i * 4 + 2]),
                       "r"(pk[i * 4 + 3]) : "memory");
    }
    if (sbar >= 0) mbar_arrive_warp(c.bar + sbar);
}

__device__ __forceinline__ void pin(const uint32_t* r, const Ctx& c) {
    asm volatile("{\n\t.reg .pred q;\n\tsetp.ne.u32 q, %12, 7;\n\t@q bra.uni PIN_SKIP;\n\t"
                 "st.volatile.shared.v4.b32 [%13], {%0, %1, %2, %3};\n\tst.volatile.shared.v4.b32 [%13], {%4, %5, %6, %7};\n\t"
                 "st.volatile.shared.v4.b32 [%13], {%8, %9, %10, %11};\n\tPIN_SKIP:\n\t}"
                 ::"r"(r[0]), "r"(r[1]), "r"(r[2]), "r"(r[3]), "r"(r[4]), "r"(r[5]), "r"(r[6]), "r"(r[7]), "r"(r[8]), "r"(r[9]),
                   "r"(r[10]), "r"(r[11]), "r"(c.wg), "r"(c.bar) : "memory");
}
__device__ __forceinline__ void acc_add(float& d, float x, float k) {
    asm volatile("fma.rn.f32 %0, %1, %2, %0;" : "+f"(d) : "f"(x), "f"(k));
}
__device__ __forceinline__ void acc_scale_add(float& d, float k, float x) {
    asm volatile("fma.rn.f32 %0, %0, %2, %1;" : "+f"(d) : "f"(x), "f"(k));
}
template <int I0, int I1>
__device__ __forceinline__ void butterfly(float (&s)[48], float (&b)[48]) {
#pragma unroll
    for (int i = I0; i < I1; ++i) {
        acc_add(s[i], b[i], 2.f / 3.f);
        acc_scale_add(b[i], -4.f / 3.f, s[i]);
    }
}
template <int RANK, int I0 = 0, int I1 = 24>
__device__ __forceinline__ void mid_row(float (&b)[48], const float (&k)[48], uint32_t (&ps)[12], uint32_t (&pk)[12],
                                        float f = 4.f / 3.f) {
#pragma unroll
    for (int i = I0; i < I1; ++i) {
        const int ch = i >> 2, o = ((ch % 3) * 4 + (i & 3)) * 4 + (ch / 3) * 2;
        acc_add(b[o], k[o], f);
        acc_add(b[o + 1], k[o + 1], f);
        uint32_t& dst = (i / 12 == RANK) ? pk[i % 12] : ps[i % 12];
        dst = pack_bf16(b[o], b[o + 1]);
        asm volatile("" : "+r"(dst));
    }
}

__device__ __forceinline__ void stagger_lead(const Ctx& c, uint32_t id) {
    asm volatile("{\n\t.reg .pred p;\n\tsetp.eq.u32 p, %1, 0;\n\t@p bar.arrive %0, 256;\n\t}" ::"r"(id), "r"(c.wg) : "memory");
}
__device__ __forceinline__ void stagger_lag(const Ctx& c, uint32_t id) {
    asm volatile("{\n\t.reg .pred p;\n\tsetp.ne.u32 p, %1, 0;\n\t@p bar.sync %0, 256;\n\t}" ::"r"(id), "r"(c.wg) : "memory");
}

#define FT_BASE 360
template <int RANK, bool LEAD>
__device__ __forceinline__ void phase1b(Ctx& c, float (&accS)[48], float (&accK)[48], float (&accC)[48],
                                        uint32_t (&d0)[24], uint32_t (&d1)[24], const uint32_t (&d2)[24],
                                        const uint32_t (&u)[24], uint32_t (&qh)[12]) {
    uint32_t qd[12];
    wgmma_wait<1>();
    mma3u(accK, u, qd, c, 0);
    sb(c);
    mbar_wait(c.bar + B_FULLA, (c.k & 1) ^ 1); FTM;
    const uint32_t last = (c.k + 16 - (NIT - 2)) >> 4;
    if (RANK == 0) ld_chunk_t<SL4, 0>(d1, c, c.ua - last * 2 * (SL4 - SL0), 0);
    else ld_chunk(d0, c, SL0, 0);
    wgmma_wait<1>(); FTM;
    mma3u(accK, u, qd, c, 1);
    sb(c);
    butterfly<0, 24>(accS, accC);
    mma3u(accK, u, qd, c, 2);
    sb(c);
    if (LEAD) stagger_lead(c, c.k + 1);
    butterfly<24, 48>(accS, accC);
    if (RANK == 0) make_quads<-1>(qh, d1, d2, u, 0, 0xc000c000u - last * (0xc000c000u - 0x3f003f00u));
    else make_quads<0>(qh, d0, d2, u, 0);
    if (ZEND) sbz(c); else sb(c);
    ++c.k;
}

#undef FT_BASE
#define FT_BASE 538
template <int RANK>
__device__ __forceinline__ void consumer(Ctx& c) {
    float accS[48], accK[48], accC[48];
    uint32_t d0[24], d1[24], d2[24], u[24];
    uint32_t qh[12];
#pragma unroll
    for (int i = 0; i < 48; ++i) { accS[i] = 0.f; accK[i] = 0.f; accC[i] = 0.f; }
    {
        uint32_t qa[12], qd[12], qe[12];
        mbar_wait(c.bar + B_FULL0, 0);
        c.rk = RANK;
        sbz(c);
        const uint32_t xo = (uint32_t)(OFF_X - OFF_IN) - c.wg * (4 * IN_ROW - X_BYTES);
        ld_chunk_t<0, 0>(d1, c, c.ua + xo, 0);
        ld_chunk(u, c, SL3, 0);
        ld_chunk_t<0, 1>(d1, c, c.ua + xo, 0);
        ld_chunk(u, c, SL3, 1);
        ld_chunk_t<0, 2>(d1, c, 0, xo + 2 * IN_SLAB - IN_B);
        ld_chunk(u, c, SL3, 2);
#pragma unroll
        for (int i = 0; i < 24; ++i) u[i] = bf2_sub(u[i], d1[i]);
#pragma unroll
        for (int kc = 0; kc < 3; ++kc) make_dup(qd, u, c, kc);
        TL(18);
        mbar_wait(c.wready, 0);
        TL(19);
#pragma unroll
        for (int kc = 0; kc < 3; ++kc) mma3d(accK, u, qd, c, 3, kc);
        mbar_wait(c.bar + B_FULLC, 0);
        ld_chunk(d2, c, SL2, 0);
        ld_chunk(d0, c, SL3, 0);
        ld_chunk(d2, c, SL2, 1);
        ld_chunk(d0, c, SL3, 1);
#pragma unroll
        for (int kc = 0; kc < 3; ++kc) {
            if (kc == 1) { sb(c); ld_chunk(d2, c, SL2, 2); ld_chunk(d0, c, SL3, 2); }
            if (kc == 2) wgmma_wait<2>();
#pragma unroll
            for (int i = kc * 8; i < kc * 8 + 8; ++i) {
                asm volatile("sub.rn.bf16x2 %0, %1, %0;" : "+r"(d0[i]) : "r"(d2[i]));
                asm volatile("fma.rn.bf16x2 %0, %0, %2, %1;" : "+r"(d1[i]) : "r"(d0[i]), "r"(0x40004000u));
                asm volatile("fma.rn.bf16x2 %0, %0, %2, %1;" : "+r"(d0[i]) : "r"(u[i]), "r"(0x3fc03fc0u));
            }
            make_dup(qa, d0, c, kc);
            mma3d(accC, d0, qa, c, 2, kc);
        }
        mbar_arrive_warp(c.bar + B_EMPTYB);
#pragma unroll
        for (int kc = 0; kc < 3; ++kc) {
            if (kc == 0) wgmma_wait<PW0>();
            if (kc >= 1) wgmma_wait<1>();
            make_dup(qe, d1, c, kc);
            mma3d(accS, d1, qe, c, 1, kc);
        }
        if (DEFW) mbar_wait(c.wready + 8, 0);
        mbar_wait(c.bar + B_FULLA, 0);
        wgmma_wait<PW1>();
        if (RANK == 0) {
            ld_chunk(d1, c, SL4, 0);
            make_quads<4>(qh, d1, d2, u, 0);
        } else {
            ld_chunk(d0, c, SL0, 0);
            make_quads<0>(qh, d0, d2, u, 0);
        }
        wgmma_wait<0>();
        sb(c);
#pragma unroll
        for (int i = 0; i < 24; ++i) d2[i] = opaque_add(d2[i], c.zero);
        fence_regs(accS);
        butterfly<0, 48>(accS, accC);
        c.k = c.zero;
        TL(23);
    }
    constexpr int KA = RANK == 0 ? 4 : 0, KB = 4 - KA;
    constexpr int SA = RANK == 0 ? SL4 : SL0, SB = RANK == 0 ? SL0 : SL4;
    uint32_t (&ea)[24] = RANK == 0 ? d1 : d0;
    uint32_t (&eb)[24] = RANK == 0 ? d0 : d1;
#pragma unroll 1
    while (c.k < NIT - 1) {
#define par(n) ((c.k + (c.zero >> n)) & 1)
        uint32_t qa[12], qb[12], qe[12], hs[12], hk[12];
        FTM;
        if (!ZEND) sbz(c);
        fence_regs(accK);
        mid_row<RANK>(accC, accK, hs, hk);
        pin(hk, c);
        uint32_t hv[12], pa[12], pb[12], va[12], vb[12];
#define AT(i) (int)(((RANK == 0 ? (i < 16 ? PLA0 : PLB0) : (i < 16 ? PLA1 : PLB1)) >> (60 - 4 * (i & 15))) & 15)
#define SLOT(n)                                                                                   \
        if (AT(2) == n && FMODE != 1) mbar_wait(c.bar + B_FULL0 + FMODE * 8, par(n));             \
        if (AT(5) == n && FMODE != 2) mbar_wait(c.bar + B_FULLB, par(n));                         \
        if (AT(14) == n) mbar_wait(c.bar + B_HFULL, par(n));                                      \
        if (AT(22) == n) mbar_wait(c.bar + B_FFULL, par(n));                                      \
        if (HPIN && n == 6) pin(hv, c);                                                           \
        if (n == 2 && !MEF) mbar_arrive_warp(c.bar + B_EMPTYE);                                        \
        if (n == 5) mbar_arrive_warp(c.bar + B_EMPTYF);                                           \
        if (n == EBSLOT) mbar_arrive_warp(c.bar + B_EMPTYB);                                      \
        if (!LLATE(n)) { LOADS(n) }                                                               \
        if (!LATE(n)) { STORES(n) }
#define LOADS(n)                                                                                  \
        if (AT(0) == n) ld_chunk(ea, c, SA, 1);                                                   \
        if (AT(1) == n) ld_chunk(ea, c, SA, 2);                                                   \
        if (AT(2) == n) ld_chunk(eb, c, SB, 0);                                                   \
        if (AT(3) == n) ld_chunk(eb, c, SB, 1);                                                   \
        if (AT(4) == n) ld_chunk(eb, c, SB, 2);                                                   \
        if (AT(5) == n) ld_chunk(u, c, SL3, 0);                                                   \
        if (AT(6) == n) ld_chunk(d2, c, SL2, 0);                                                  \
        if (AT(7) == n) ld_chunk(u, c, SL3, 1);                                                   \
        if (AT(8) == n) ld_chunk(d2, c, SL2, 1);                                                  \
        if (AT(9) == n) ld_chunk(u, c, SL3, 2);                                                   \
        if (AT(10) == n) ld_chunk(d2, c, SL2, 2);                                                 \
        if (AT(14) == n) fin_load<3>(hv, c, 2 * X_UNIT);                                          \
        if (AT(22) == n) fin_load<3>(va, c, 0);                                                   \
        if (AT(24) == n) fin_load<3>(vb, c, X_UNIT);
#define STORES(n)                                                                                 \
        if (AT(15) == n) { if (HPIN) fin_store<3>(hv, hk, c, 2 * X_UNIT, B_SH); else fin_store<3>(hk, hv, c, 2 * X_UNIT, B_SH); } \
        if (AT(23) == n) fin_store<3>(pa, va, c, 0, -1);                                          \
        if (AT(25) == n) fin_store<3>(pb, vb, c, X_UNIT, B_SF);                                   \
        if (LLATE(n) && !LLATE2(n)) { LOADS(n) }                                                                \
        if (AT(11) == n) send_half<0>(hs, c, n);                                                  \
        if (AT(12) == n) send_half<1>(hs, c, n);                                                  \
        if (AT(13) == n) send_half<2>(hs, c, n);                                                  \
        if (AT(16) == n) send_acc<0, 1, 0>(accS, c, n);                                           \
        if (AT(17) == n) send_acc<3, 4, 0>(accS, c, n);                                           \
        if (AT(18) == n) send_acc<1, 2, 0>(accS, c, n);                                           \
        if (AT(19) == n) send_acc<4, 5, 0>(accS, c, n);                                           \
        if (AT(20) == n) send_acc<2, 3, 0>(accS, c, n);                                           \
        if (AT(21) == n) send_acc<5, 6, 0>(accS, c, n);                                           \
        if (LLATE(n) && LLATE2(n)) { LOADS(n) }                                                   \
        if (n == PKSLOT) { fin_pack<0, 3>(accK, pa); fin_pack<3, 3>(accK, pb); pin(pa, c); pin(pb, c); }
#define QW(n, Q)                                                                     \
        if (LATE(n)) { Q; sb(c); STORES(n); sb(c); wgmma_wait<1 + NW(n)>(); FTW(n); }        \
        else if (EQ(n)) { Q; sb(c); wgmma_wait<1 + NW(n)>(); FTW(n); } else { sb(c); wgmma_wait<1 + NW(n)>(); FTW(n); Q; } \
        if (LAGPOS == n) stagger_lag(c, c.k + 1);
#define P1(g, q)                                                                                  \
        SLOT(g + 5);                                                                              \
        if (PG(g) < 4) {                                                                          \
            QW(g + 5, make_mid<true>(q, d1, d2, u, PG(g) & 3, u));                                 \
            mma3(accC, q, c, 2, PG(g) & 3, g == 0);                                               \
        } else {                                                                                  \
            QW(g + 5, make_dup(qe, d1, c, PG(g) & 3));                                            \
            mma3d(accS, d1, qe, c, 1, PG(g) & 3, M1FIRST);                                        \
        }
        SLOT(15);
        sbk(c);
#pragma unroll
        for (int i = 0; i < 48; ++i) {
            acc_add(accS[i], accK[i], RANK == 0 ? 8.f / 3.f : 2.f / 3.f);
            acc_scale_add(accK[i], RANK == 0 ? -2.f : 2.f, accS[i]);
        }
        FTM;
        mma3(accS, qh, c, KA, 0, false);
        sb(c);
        SLOT(0);
        make_quads<KA>(qa, ea, d2, u, 1);
        mma3(accS, qa, c, KA, 1, false);
        sb(c);
        SLOT(1);
        QW(1, make_quads<KA>(qb, ea, d2, u, 2));
        mma3(accS, qb, c, KA, 2, false);
        sb(c);
        SLOT(2);
        QW(2, make_quads<KB>(qa, eb, d2, u, 0));
        mma3(accK, qa, c, KB, 0, false);
        sb(c);
        SLOT(3);
        QW(3, make_quads<KB>(qb, eb, d2, u, 1));
        mma3(accK, qb, c, KB, 1, false);
        sb(c);
        SLOT(4);
        QW(4, make_quads<KB>(qa, eb, d2, u, 2));
        mma3(accK, qa, c, KB, 2, false);
        sb(c);
        P1(0, qb);

        sb(c);
        P1(1, qa);

        sb(c);
        P1(2, qb);

        sb(c);
        P1(3, qa);

        sb(c);
        P1(4, qb);

        sb(c);
        P1(5, qa);

        sb(c);
        SLOT(11);
        if (LAGPOS == 11) stagger_lag(c, c.k + 1);
        phase1b<RANK, true>(c, accS, accK, accC, d0, d1, d2, u, qh);
        wgmma_wait<0>();
        TL(1 + c.k);
#undef par
    }
    {
        constexpr uint32_t par = (NIT - 1) & 1;
        uint32_t qa[12], qb[12], hs[12], hk[12], v[12];
        constexpr int S0 = 12 - 12 * RANK, K0 = 12 * RANK;
        uint32_t pk[12];
        ld_chunk(d0, c, SL0, 1);
        ld_chunk(d0, c, SL0, 2);
        mma3(accS, qh, c, 0, 0, false);
        fence_regs(accK);
        mid_row<RANK, S0, S0 + 12>(accC, accK, hs, hk);
        send_half<0>(hs, c);
        send_half<1>(hs, c);
        send_half<2>(hs, c);
        sb(c);
        make_quads<0>(qa, d0, d2, u, 1);
        mma3(accS, qa, c, 0, 1, false);
        make_quads<0>(qb, d0, d2, u, 2);
        mma3(accS, qb, c, 0, 2, false);
        mid_row<RANK, K0, K0 + 12>(accC, accK, hs, hk);
        mbar_wait(c.bar + B_FULLB, par);
        wgmma_wait<0>();
        fence_regs(accS);
        mid_row<RANK, S0, S0 + 12>(accS, accK, hs, pk, 2.f / 3.f);
        send_half<0, false>(hs, c);
        send_half<1, false>(hs, c);
        send_half<2, false>(hs, c);
        mbar_wait(c.bar + B_HFULL, par);
        fin_load<3>(v, c, 2 * X_UNIT);
        mid_row<RANK, K0, K0 + 12>(accS, accK, hs, pk, 2.f / 3.f);
        fin_store<3>(hk, v, c, 2 * X_UNIT, B_SH);
        mbar_wait(c.bar + B_FFULL + c.zero, par);
        fin_load<3>(v, c, 0);
        fin_store<3>(pk, v, c, 0, B_SF);
        TL(17);
    }
}

__device__ __forceinline__ void wt_load(uint32_t (&g)[36], uint32_t unit, int lane) {
    const uint32_t src = unit + (lane >> 2) * 192 + ((lane & 3) << 4);
#pragma unroll
    for (int i = 0; i < 9; ++i)
        asm volatile("ld.shared.v4.b32 {%0, %1, %2, %3}, [%4];"
                     : "=r"(g[i * 4]), "=r"(g[i * 4 + 1]), "=r"(g[i * 4 + 2]), "=r"(g[i * 4 + 3])
                     : "r"(src + (i / 3) * 64 + (i % 3) * 2 * W_COMP) : "memory");
}
__device__ __forceinline__ void stsm(uint32_t addr, const uint32_t* v) {
    asm volatile("stmatrix.sync.aligned.m8n8.x4.shared.b16 [%0], {%1, %2, %3, %4};"
                 ::"r"(addr), "r"(v[0]), "r"(v[1]), "r"(v[2]), "r"(v[3]) : "memory");
}
template <int PART>
__device__ __forceinline__ void wt_store(const uint32_t (&g)[36], uint32_t unit, int lane) {
    const uint32_t dst = unit + (lane & 7) * 64 + ((((lane >> 3) ^ (lane >> 1)) & 3) << 4);
    __syncwarp();
#pragma unroll
    for (int r = 0; r < 3; ++r) {
        const uint32_t *a = &g[r * 12], *b = a + 4, *cc = a + 8;
        uint32_t u1[4], u2[4], u3[4];
#pragma unroll
        for (int i = 0; i < 4; ++i) {
            uint32_t h;
            asm("add.rn.bf16x2 %0, %1, %2;" : "=r"(h) : "r"(a[i]), "r"(cc[i]));
            asm("mul.rn.bf16x2 %0, %1, %2;" : "=r"(h) : "r"(h), "r"(0x3f003f00u));
            asm("fma.rn.bf16x2 %0, %1, %2, %3;" : "=r"(u1[i]) : "r"(b[i]), "r"(0x3f003f00u), "r"(h));
            asm("fma.rn.bf16x2 %0, %1, %2, %3;" : "=r"(u2[i]) : "r"(b[i]), "r"(0xbf00bf00u), "r"(h));
            asm("fma.rn.bf16x2 %0, %1, %2, %3;" : "=r"(h) : "r"(a[i]), "r"(0x3e803e80u), "r"(cc[i]));
            asm("fma.rn.bf16x2 %0, %1, %2, %3;" : "=r"(u3[i]) : "r"(b[i]), "r"(0x3f003f00u), "r"(h));
        }
        if (PART & 1) {
            stsm(dst + r * 512 + CP(2) * W_COMP, u2);
            stsm(dst + r * 512 + CP(1) * W_COMP, u1);
            stsm(dst + r * 512 + CP(3) * W_COMP, u3);
        }
        if (PART & 2) {
            stsm(dst + r * 512 + CP(0) * W_COMP, a);
            stsm(dst + r * 512 + CP(4) * W_COMP, cc);
        }
    }
}

__device__ __forceinline__ int seq_row(int seg, int row_par, int n) {
    const int q = (seg & 1) ? seg * SEG - 1 + n : seg * SEG + SEG - n;
    return 2 * q + row_par;
}

struct XMaps { CUtensorMap m[2]; };
#define xmap xm.m[0]
__global__ void __cluster_dims__(2, 1, 1) __launch_bounds__(384, 1)
conv_kernel(const __grid_constant__ XMaps xm, const __grid_constant__ CUtensorMap omap,
            const char* __restrict__ wp, const char* __restrict__ xp) {
    extern __shared__ uint8_t smem_raw[];
    const uint32_t base = (smem_u32(smem_raw) + 1023u) & ~1023u;
    const uint32_t wbase = base + OFF_W;
    const uint32_t bar_base = base + OFF_BAR;
    const uint32_t wbar_b = bar_base + 256, wready_b = bar_base + 280;

    const int tid = threadIdx.x;
    const int warp = tid >> 5, lane = tid & 31;
    const int rank = blockIdx.x & 1;
    const int cluster = blockIdx.x >> 1;
    const int strip = cluster & 7, seg = cluster >> 3;
    const int fmode = rank ? FMODE1 : FMODE0;
    uint32_t c_start;
    asm volatile("mov.u32 %0, %clock;" : "=r"(c_start) :: "memory");

    if (warp == 3) {
        if (lane < 20) {
            const char* p = wp + (size_t)(((blockIdx.x & 63) * 20 + lane + (blockIdx.x >> 6) * 16) * 128);
            asm volatile("prefetch.global.L2 [%0];" ::"l"(p) : "memory");
        }
        if (lane < 2) asm volatile("prefetch.tensormap [%0];" ::"l"((uint64_t)(&xmap + lane)) : "memory");
    }
    if (tid == 0) {
        for (int i = 0; i < 3; ++i) mbar_init(wbar_b + i * 8, 1);
        asm volatile("fence.mbarrier_init.release.cluster;" ::: "memory");
        asm volatile("fence.proxy.async.shared::cta;" ::: "memory");
    }
#define RT 320
    if (tid == RT) {
        for (int i = 0; i < 4; ++i) mbar_init(bar_base + (i >> 1) * 128 + (i & 1) * B_FULLC, 1);
        asm volatile("fence.mbarrier_init.release.cluster;" ::: "memory");
        asm volatile("fence.proxy.async.shared::cta;" ::: "memory");
    }
    if (tid == 64) {
        for (int i = 0; i < 2; ++i) {
            mbar_init(bar_base + i * 128 + B_FULLA, (fmode == 1 ? 2 : 1) + DEC);
            mbar_init(bar_base + i * 128 + B_FULLB, (fmode == 2 ? 2 : 1) + DEC);
            mbar_init(bar_base + i * 128 + B_EMPTYE, 4);
            mbar_init(bar_base + i * 128 + B_EMPTYF, 4);
            mbar_init(bar_base + i * 128 + B_EMPTYB, 4);
            mbar_init(bar_base + i * 128 + B_HFULL, 1);
            mbar_init(bar_base + i * 128 + B_FFULL, 1);
            mbar_init(bar_base + i * 128 + B_SH, 4);
            mbar_init(bar_base + i * 128 + B_SF, 4);
            mbar_expect_tx(bar_base + i * 128 + B_HFULL, X_TX);
            if (DEC) {
                mbar_expect_tx(bar_base + i * 128 + B_FFULL, 2 * X_TX);
                mbar_arrive(bar_base + i * 128 + B_FULLA);
                mbar_arrive(bar_base + i * 128 + B_FULLB);
            }
        }
        mbar_init(wready_b, 8);
        mbar_init(wready_b + 8, 8);
        asm volatile("fence.mbarrier_init.release.cluster;" ::: "memory");
        asm volatile("fence.proxy.async.shared::cta;" ::: "memory");
    }
    __syncwarp();
    asm volatile("barrier.cluster.arrive.relaxed.aligned;" ::: "memory");
    if (tid == 0) {
        const int up = (seg & 1) ^ 1;
#pragma unroll 1
        for (int j = 0; j < 3; ++j) {
            mbar_expect_tx(wbar_b + j * 8, 3 * W_TAP);
#pragma unroll
            for (int i = 0; i < 3; ++i)
                asm volatile("cp.async.bulk.shared::cluster.global.mbarrier::complete_tx::bytes [%0], [%1], %2, [%3];"
                             ::"r"(wbase + ((up ? 2 - i : i) * 6 + j) * W_TAP), "l"(wp + (2 * (i * 3 + j) + rank) * W_TAP),
                               "r"(W_TAP), "r"(wbar_b + j * 8) : "memory");
        }
    }
    if (tid == RT) {
#pragma unroll 1
        for (int i = 0; i < 6; ++i) {
            const int wg = (RORD >> (i * 4 + 2)) & 1, n = (RORD >> (i * 4)) & 3;
            const uint32_t fb = bar_base + wg * 128 + (n == 2 ? B_FULLC : B_FULL0);
            while ((uint32_t)clock() - c_start < ROW_DELAY) {}
            if (n != 3) mbar_expect_tx(fb, (3 - n) * IN_ROW);
            const uint32_t dst = base + (n == 1 ? OFF_X + wg * X_BYTES : OFF_IN + wg * 4 * IN_ROW + n * 2 * IN_SLAB);
            load_row(dst, dst + (n == 1 ? 2 * IN_SLAB : IN_B - n * IN_SLAB), &xmap, fb, rank, strip, seq_row(seg, wg, n), true);
        }
    }
    __syncwarp();
#define ST(j)
    ST(0);

    if (warp >= 8) {
        asm volatile("setmaxnreg.dec.sync.aligned.u32 24;");
        asm volatile("barrier.cluster.wait.aligned;" ::: "memory");
        if (lane == 0) {
            const int wg = warp & 1;
            const uint32_t bar = bar_base + wg * 128;
            if (warp < 10) {
                const uint32_t in = base + OFF_IN + wg * 4 * IN_ROW;
#pragma unroll 1
                for (int i = 0; i < 3 * NIT; ++i) {
                    const int t = i / 3, g = i - 3 * t;
                    const int sl = g == 2 ? 2 : (g ^ rank ^ 1);
                    const uint32_t fb = bar + (g == 0 ? B_FULLA : g == 2 ? B_FULLB : B_FULL0 + fmode * 8);
                    {
                        const int n = i + PF, row = seq_row(seg, wg, n);
                        if (i >= PF0 && n < SEG + 2 && (unsigned)row < IMG_H)
                            asm volatile("cp.async.bulk.prefetch.L2.global [%0], %1;"
                                         ::"l"(xp + ((size_t)row * IMG_W + strip * 64 + rank * 32) * 192), "r"(32 * 192) : "memory");
                    }
                    mbar_wait(bar + B_EMPTYE + (MEF && g == 0 ? 1 : g) * 8, t & 1);
                    if (t == NIT - 1 && sl != 0) {
                        mbar_arrive(fb);
                    } else {
                        mbar_expect_tx(fb, g == 2 ? 2 * IN_ROW : IN_ROW);
                        if (g == 2) load_row(in + 2 * SL3, in + IN_B + SL3, &xmap, fb, rank, strip, seq_row(seg, wg, 3 * t + 6), true);
#define LD_EF 0
                        load_row(in + sl * 2 * IN_SLAB, in + IN_B + sl * IN_SLAB, &xmap, fb, rank, strip, seq_row(seg, wg, 3 * t + (sl == 0 ? 0 : 3 + sl)),
                                 LD_EF == 3 ? g != 1 : LD_EF == 4 ? g == 0 : LD_EF == 5 ? (g == 0 || (g == 2 && rank == 0)) : LD_EF == 6 ? (g == 0 || (g == 2 && rank == 1)) : LD_EF == 7 ? sl != 0 : false);
                    }
                }
            } else {
                const uint32_t src = base + OFF_X + wg * X_BYTES;
                const uint32_t r_bar = mapa(bar, rank ^ 1);
                if (wg == 0)
                    for (int i = 0; i < 4; ++i)
                        asm volatile("mbarrier.arrive.shared::cta.b64 _, [%0], 4;" ::"r"(bar + (i >> 1) * 128 + B_EMPTYE + (i & 1) * 8) : "memory");
#pragma unroll 1
                for (int t = 0; t < NIT; ++t) {
                    const bool last = t == NIT - 1;
                    if (last && !DEC) mbar_expect_tx(bar + B_FFULL, X_TX);
                    mbar_wait(bar + B_SH, t & 1);
                    asm volatile("fence.proxy.async.shared::cta;" ::: "memory");
                    tma_store_4d(&omap, src + 2 * X_UNIT, 0, strip * 16, rank, seq_row(seg, wg, 3 * t + 2));
                    asm volatile("cp.async.bulk.commit_group;" ::: "memory");
                    if (!last) {
                        if (DEC) mbar_expect_tx(bar + B_HFULL, X_TX);
                        asm volatile("cp.async.bulk.wait_group.read 0;" ::: "memory");
                        if (DEC) mbar_arrive_remote(r_bar + B_FULLA);
                        else mbar_expect_tx_remote(r_bar + B_FFULL, 2 * X_TX);
                    }
                    mbar_wait(bar + B_SF, t & 1);
                    asm volatile("fence.proxy.async.shared::cta;" ::: "memory");
                    const int orow = seq_row(seg, wg, 3 * t + 1 + (last ? 0 : 2 * rank));
                    tma_store_4d(&omap, src, 0, strip * 16, last ? rank : 0, orow);
                    if (!last) tma_store_4d(&omap, src + X_UNIT, 0, strip * 16, 1, orow);
                    asm volatile("cp.async.bulk.commit_group;" ::: "memory");
                    if (DEC && !last) mbar_expect_tx(bar + B_FFULL, t == NIT - 2 ? X_TX : 2 * X_TX);
                    asm volatile("cp.async.bulk.wait_group.read 0;" ::: "memory");
                    if (!last) {
                        if (DEC) mbar_arrive_remote(r_bar + B_FULLB);
                        else mbar_expect_tx_remote(r_bar + B_HFULL, X_TX);
                    }
                }
            }
        }
    } else {
        if (RT < 256) asm volatile("setmaxnreg.inc.sync.aligned.u32 240;");
        asm volatile("barrier.cluster.wait.aligned;" ::: "memory");
        const int uwarp = __shfl_sync(0xffffffffu, warp, 0);
        const int wg = uwarp >> 2;
        const int w4 = warp & 3;
        {
            uint32_t ga[36], gb[36];
#define WX 4
            const int uw = uwarp ^ WX;
            const uint32_t unit = wbase + uw * W_K8;
            ST(1);
            mbar_wait(wbar_b + (uw < 6 ? 0 : 8), 0);
            ST(2);
            wt_load(ga, unit, lane);
            mbar_wait(wbar_b + (uw < 4 ? 8 : 16), 0);
            ST(3);
            wt_load(gb, unit + 8 * W_K8, lane);
            wt_store<3>(ga, unit, lane);
            ST(4);
            if (uw < 2) {
                mbar_wait(wbar_b + 16, 0);
                wt_load(ga, unit + 16 * W_K8, lane);
            }
            wt_store<3>(gb, unit + 8 * W_K8, lane);
            if (uw < 2) wt_store<3>(ga, unit + 16 * W_K8, lane);
            ST(5);
            asm volatile("fence.proxy.async.shared::cta;" ::: "memory");
            mbar_arrive_warp(wready_b);
            ST(6);
        }
        if (RT >= 256) asm volatile("setmaxnreg.inc.sync.aligned.u32 240;");
        ST(7);
        Ctx c;
        c.bar = bar_base + wg * 128;
        c.wdesc = ((wbase & 0x3FFFF) >> 4) | ((uint32_t)(512 >> 4) << 16);
        c.wready = wready_b;
        c.wg = wg;
        c.k = ~0u;
        c.zero = 0;
        c.tlo2 = bar_base + 576 - bar_base * 4;
        c.tlo = 320;
        {
            const int m = lane >> 3, gg = lane & 7, hl = m >> 1;
            const int rho0 = (m & 1) ? (8 * w4 + gg + 2) : (36 + 8 * w4 + gg);
            const int rho1 = rho0 + 2;
            const uint32_t in = base + OFF_IN + wg * 4 * IN_ROW;
            c.ld0 = in + IN_B + rho0 * 32 + ((hl ^ ((rho0 >> 2) & 1)) << 4);
            c.ld1 = in + IN_B + rho1 * 32 + ((hl ^ ((rho1 >> 2) & 1)) << 4);
            c.vz = (rho0 & 2) << 3;
            c.ua = in - 2 * (in + IN_B);
        }
        c.xbuf = base + OFF_X + wg * X_BYTES + (tid & 127) * 16;
        c.r_off = mapa(c.bar, rank ^ 1) - c.bar;
        c.ld0 = __shfl_sync(0xffffffffu, c.ld0, lane);
        c.ld1 = __shfl_sync(0xffffffffu, c.ld1, lane);
        c.xbuf = __shfl_sync(0xffffffffu, c.xbuf, lane);
        TL(1);
        TLC(20);
        if (rank == 0) consumer<0>(c);
        else consumer<1>(c);
        TLC(21);
    }
}

typedef CUresult (*EncodeFn)(CUtensorMap*, CUtensorMapDataType, cuuint32_t, void*, const cuuint64_t*,
                             const cuuint64_t*, const cuuint32_t*, const cuuint32_t*, CUtensorMapInterleave,
                             CUtensorMapSwizzle, CUtensorMapL2promotion, CUtensorMapFloatOOBfill);

}

extern "C" void kernel_launch(void* const* d_in, const int* in_sizes, int n_in, void* d_out, int out_size) {
    (void)in_sizes; (void)n_in; (void)out_size;
    static EncodeFn encode = nullptr;
    if (!encode) {
        void* fn = nullptr;
        cudaDriverEntryPointQueryResult qres;
        cudaGetDriverEntryPoint("cuTensorMapEncodeTiled", &fn, cudaEnableDefault, &qres);
        encode = (EncodeFn)fn;
        cudaFuncSetAttribute(conv_kernel, cudaFuncAttributeMaxDynamicSharedMemorySize, SMEM_BYTES);
    }
    XMaps xm;
    CUtensorMap omap;
    cuuint32_t estr5[5] = {1, 1, 1, 1, 1};
    {
        cuuint64_t dims[5] = {(cuuint64_t)CH, 2, (cuuint64_t)IMG_W / 4, 2, (cuuint64_t)IMG_H};
        cuuint64_t strides[4] = {(cuuint64_t)CH * 2, (cuuint64_t)CH * 2 * 4, (cuuint64_t)CH * 2 * 2,
                                 (cuuint64_t)IMG_W * CH * 2};
        cuuint32_t box[5] = {16, 2, 18, 2, 1};
        encode(&xmap, CU_TENSOR_MAP_DATA_TYPE_BFLOAT16, 5, d_in[0], dims, strides, box, estr5,
               CU_TENSOR_MAP_INTERLEAVE_NONE, CU_TENSOR_MAP_SWIZZLE_32B, PROMO,
               CU_TENSOR_MAP_FLOAT_OOB_FILL_NONE);
        box[0] = 32;
        encode(&xm.m[1], CU_TENSOR_MAP_DATA_TYPE_BFLOAT16, 5, d_in[0], dims, strides, box, estr5,
               CU_TENSOR_MAP_INTERLEAVE_NONE, CU_TENSOR_MAP_SWIZZLE_64B, PROMO,
               CU_TENSOR_MAP_FLOAT_OOB_FILL_NONE);
    }
    {
        cuuint64_t dims[5] = {32, 2, (cuuint64_t)IMG_H * IMG_W / 4, 3, 2};
        cuuint64_t strides[4] = {(cuuint64_t)CH * 2, (cuuint64_t)CH * 2 * 4, 64, (cuuint64_t)CH * 2 * 2};
        cuuint32_t box[5] = {32, 2, 16, 3, 1};
        encode(&omap, CU_TENSOR_MAP_DATA_TYPE_BFLOAT16, 5, d_out, dims, strides, box, estr5,
               CU_TENSOR_MAP_INTERLEAVE_NONE, CU_TENSOR_MAP_SWIZZLE_NONE, CU_TENSOR_MAP_L2_PROMOTION_NONE,
               CU_TENSOR_MAP_FLOAT_OOB_FILL_NONE);
    }
    conv_kernel<<<NUM_CTAS, 384, SMEM_BYTES>>>(xm, omap, (const char*)d_in[1], (const char*)d_in[0]);
}
```

```cpp
#include <cuda_runtime.h>
#include <cuda_bf16.h>
#include <cuda.h>
#include <stdint.h>

namespace {

#define ST_EF
#define PF 6
#define PF0 5
#define EQ0 0x7fe
#define EQ1 0x7fe
#define PLA0 0xf0122334455fff45ull
#define PLA1 0xff012334455fff45ull
#define PLB0 0x3333339aab000000ull
#define PLB1 0x3333449aab000000ull
#define FMODE0 1
#define FMODE1 1
#define ORD 0
#define FMODE (RANK == 0 ? FMODE0 : FMODE1)
#define LT0 0
#define LT1 0x10
#define LATE(n) (((RANK == 0 ? LT0 : LT1) >> (n)) & 1)
#define LL0 0x20
#define LL1 0x30
#define LLATE(n) (((RANK == 0 ? LL0 : LL1) >> (n)) & 1)
#define PO0 0x012654
#define PO1 PO0
#define PG(g) (((RANK == 0 ? PO0 : PO1) >> (20 - (g) * 4)) & 7)
#define M1FIRST (PG(2) >= 4 ? PG(2) & 3 : PG(3) & 3)
#define EBSLOT (PG(2) == 2 ? 8 : PG(3) == 2 ? 9 : 10)
#define NW0 0
#define NW1 NW0
#define NW(n) (((RANK == 0 ? NW0 : NW1) >> (n)) & 1)
#define DEC 1
#define RORD 0x675231
#define PW0 0
#define PW1 1
#define EPO 0x8c04ab9231ull
#define PROMO CU_TENSOR_MAP_L2_PROMOTION_L2_128B
#define ZEND 1
#define HPIN 0
#define LL2 0x20
#define LLATE2(n) ((LL2 >> (n)) & 1)
#define CPT 0x01234
#define CP(k) ((CPT >> (16 - 4 * (k))) & 7)
#define MEF 0
#define DEFW 0
#define PKSLOT 7
#define EQ(n) (((RANK == 0 ? EQ0 : EQ1) >> (n)) & 1)
#define LAG0 5
#define LEAD0 8
#define LAG1 LAG0
#define LEAD1 LEAD0
#define LAGPOS (RANK == 0 ? LAG0 : LAG1)
#define LEADPOS (RANK == 0 ? LEAD0 : LEAD1)
#define LAGK (LEADPOS > 20 ? 1 : LEADPOS >= 12 || LEADPOS < LAGPOS ? 2 : 1)
#define SEND1 4
#define SEND2 6
#define TL(slot)
#define TLC(slot)
constexpr int IMG_H = 512, IMG_W = 512, CH = 96;
constexpr int IN_SLAB = 72 * 32;
constexpr int IN_ROW = 3 * IN_SLAB;
constexpr int SL0 = 0, SL4 = IN_SLAB, SL2 = 2 * IN_SLAB, SL3 = 3 * IN_SLAB, IN_B = 8 * IN_SLAB;
constexpr int W_K8 = 3 * 512;
constexpr int W_TAP = 6 * W_K8;
constexpr int W_COMP = 3 * W_TAP;
constexpr int W_BYTES = 5 * W_COMP;
constexpr int X_CH = 32 * 64;
constexpr int X_UNIT = 3 * X_CH;
constexpr int X_BYTES = 3 * X_UNIT;
constexpr int X_TX = X_UNIT;
constexpr int SEG = 32;
constexpr int NIT = 11;
constexpr int NUM_CTAS = 128;
#define LAY 3
constexpr int OFF_W = LAY == 0 ? 0 : LAY == 1 ? 2 * X_BYTES : LAY == 2 ? 2 * X_BYTES + 8 * IN_ROW : 8 * IN_ROW;
constexpr int OFF_X = LAY == 0 ? W_BYTES : LAY == 3 ? W_BYTES + 8 * IN_ROW : 0;
constexpr int OFF_IN = LAY == 3 ? 0 : LAY == 2 ? 2 * X_BYTES : W_BYTES + 2 * X_BYTES;
constexpr int OFF_BAR = W_BYTES + 2 * X_BYTES + 8 * IN_ROW;
constexpr int SMEM_BYTES = 1024 + OFF_BAR + 1024;
static_assert(SMEM_BYTES <= 232448, "smem");
#define RDEL 700
constexpr uint32_t ROW_DELAY = RDEL;
constexpr int B_FULL0 = 0, B_FULLA = 8, B_FULLB = 16, B_FULLC = 24, B_EMPTYE = 32, B_EMPTYF = 40, B_EMPTYB = 48, B_HFULL = 56,
              B_FFULL = 64, B_SH = 72, B_SF = 80;

__device__ __forceinline__ uint32_t smem_u32(const void* p) {
    return (uint32_t)__cvta_generic_to_shared(p);
}
__device__ __forceinline__ void mbar_init(uint32_t bar, uint32_t count) {
    asm volatile("mbarrier.init.shared::cta.b64 [%0], %1;" ::"r"(bar), "r"(count) : "memory");
}
__device__ __forceinline__ void mbar_expect_tx(uint32_t bar, uint32_t bytes) {
    asm volatile("mbarrier.arrive.expect_tx.shared::cta.b64 _, [%0], %1;" ::"r"(bar), "r"(bytes) : "memory");
}
__device__ __forceinline__ void mbar_arrive(uint32_t bar) {
    asm volatile("mbarrier.arrive.shared::cta.b64 _, [%0];" ::"r"(bar) : "memory");
}
__device__ __forceinline__ void mbar_arrive_warp(uint32_t bar) {
    __syncwarp();
    asm volatile("{\n\t.reg .pred p;\n\telect.sync _|p, 0xffffffff;\n\t@p mbarrier.arrive.shared::cta.b64 _, [%0];\n\t}" ::"r"(bar) : "memory");
}
__device__ __forceinline__ void mbar_arrive_remote(uint32_t rbar) {
    asm volatile("mbarrier.arrive.relaxed.cluster.shared::cluster.b64 _, [%0];" ::"r"(rbar) : "memory");
}
__device__ __forceinline__ void mbar_expect_tx_remote(uint32_t rbar, uint32_t bytes) {
    asm volatile("mbarrier.arrive.expect_tx.relaxed.cluster.shared::cluster.b64 _, [%0], %1;" ::"r"(rbar), "r"(bytes) : "memory");
}
__device__ __forceinline__ void mbar_wait(uint32_t bar, uint32_t parity) {
    uint32_t done;
    for (;;) {
        asm volatile(
            "{\n\t.reg .pred p;\n\t"
            "mbarrier.try_wait.parity.shared::cta.b64 p, [%1], %2;\n\t"
            "selp.u32 %0, 1, 0, p;\n\t}"
            : "=r"(done) : "r"(bar), "r"(parity) : "memory");
        if (done) return;
    }
}
#define STAMP(t, j)
__device__ __forceinline__ uint32_t mbar_try(uint32_t bar, uint32_t parity) {
    uint32_t done;
    asm volatile("{\n\t.reg .pred p;\n\tmbarrier.try_wait.parity.shared::cta.b64 p, [%1], %2;\n\tselp.u32 %0, 1, 0, p;\n\t}"
                 : "=r"(done) : "r"(bar), "r"(parity) : "memory");
    return done;
}
#define HSL 0
__device__ __forceinline__ void mbar_wait_h(uint32_t bar, uint32_t parity) {
    mbar_wait(bar, parity);
}
__device__ __forceinline__ bool elect() {
    uint32_t el;
    asm volatile("{\n\t.reg .pred p;\n\telect.sync _|p, 0xffffffff;\n\tselp.u32 %0, 1, 0, p;\n\t}" : "=r"(el));
    return el;
}
__device__ __forceinline__ uint32_t mapa(uint32_t addr, uint32_t rank) {
    uint32_t r;
    asm("mapa.shared::cluster.u32 %0, %1, %2;" : "=r"(r) : "r"(addr), "r"(rank));
    return r;
}
__device__ __forceinline__ void tma_load_5d(uint32_t dst, const CUtensorMap* map, uint32_t bar,
                                            int c0, int c1, int c2, int c3, int c4, bool keep) {
    asm volatile(
        "cp.async.bulk.tensor.5d.shared::cluster.global.mbarrier::complete_tx::bytes "
        "[%0], [%1, {%3, %4, %5, %6, %7}], [%2];"
        ::"r"(dst), "l"((uint64_t)map), "r"(bar), "r"(c0), "r"(c1), "r"(c2), "r"(c3), "r"(c4) : "memory");
}
#define EFN 99
#define EFM 7
#define EFM2 0
#define EF(t, u) ((((t) < EFN ? EFM : EFM2) >> (u)) & 1)
__device__ __forceinline__ void tma_store_4d(const CUtensorMap* map, uint32_t src, int c0, int c1, int c2, int c3, bool ef) {
    uint64_t pol, pn;
    asm volatile("createpolicy.fractional.L2::evict_first.b64 %0, 1.0;" : "=l"(pol));
    asm volatile("createpolicy.fractional.L2::evict_normal.b64 %0, 1.0;" : "=l"(pn));
    if (!ef) pol = pn;
    asm volatile("cp.async.bulk.tensor.5d.global.shared::cta.bulk_group.L2::cache_hint [%0, {%2, %2, %3, %2, %4}], [%1], %5;"
                 ::"l"((uint64_t)map), "r"(src), "r"(c0), "r"(c3 * 128 + c1), "r"(c2), "l"(pol) : "memory");
}
__device__ __forceinline__ void load_row(uint32_t dst, uint32_t dstb, const CUtensorMap* xmap, uint32_t fb, int rank, int strip, int row, bool keep) {
    tma_load_5d(dst, xmap + 1, fb, rank * 64, 0, strip * 16 - 1, 0, row, keep);
    tma_load_5d(dstb, xmap, fb, 32 + rank * 16, 0, strip * 16 - 1, 0, row, keep);
}

__device__ __forceinline__ void wgmma_fence() { asm volatile("wgmma.fence.sync.aligned;" ::: "memory"); }
__device__ __forceinline__ void wgmma_commit() { asm volatile("wgmma.commit_group.sync.aligned;" ::: "memory"); }
template <int N>
__device__ __forceinline__ void wgmma_wait() { asm volatile("wgmma.wait_group.sync.aligned %0;" ::"n"(N) : "memory"); }

template <int SA>
__device__ __forceinline__ void wgmma_m64n96k16(float (&d)[48], const uint32_t* a, uint64_t db, int scale_d) {
    asm volatile(
        "{\n\t.reg .pred p;\n\t"
        "setp.ne.b32 p, %53, 0;\n\t"
        "wgmma.mma_async.sync.aligned.m64n96k16.f32.bf16.bf16 "
        "{%0, %1, %2, %3, %4, %5, %6, %7, %8, %9, %10, %11, %12, %13, %14, %15, "
        " %16, %17, %18, %19, %20, %21, %22, %23, %24, %25, %26, %27, %28, %29, %30, %31, "
        " %32, %33, %34, %35, %36, %37, %38, %39, %40, %41, %42, %43, %44, %45, %46, %47}, "
        "{%48, %49, %50, %51}, %52, p, %54, 1, 1;\n\t}"
        : "+f"(d[0]), "+f"(d[1]), "+f"(d[2]), "+f"(d[3]), "+f"(d[4]), "+f"(d[5]), "+f"(d[6]), "+f"(d[7]),
          "+f"(d[8]), "+f"(d[9]), "+f"(d[10]), "+f"(d[11]), "+f"(d[12]), "+f"(d[13]), "+f"(d[14]), "+f"(d[15]),
          "+f"(d[16]), "+f"(d[17]), "+f"(d[18]), "+f"(d[19]), "+f"(d[20]), "+f"(d[21]), "+f"(d[22]), "+f"(d[23]),
          "+f"(d[24]), "+f"(d[25]), "+f"(d[26]), "+f"(d[27]), "+f"(d[28]), "+f"(d[29]), "+f"(d[30]), "+f"(d[31]),
          "+f"(d[32]), "+f"(d[33]), "+f"(d[34]), "+f"(d[35]), "+f"(d[36]), "+f"(d[37]), "+f"(d[38]), "+f"(d[39]),
          "+f"(d[40]), "+f"(d[41]), "+f"(d[42]), "+f"(d[43]), "+f"(d[44]), "+f"(d[45]), "+f"(d[46]), "+f"(d[47])
        : "r"(a[0]), "r"(a[1]), "r"(a[2]), "r"(a[3]), "l"(db), "r"(scale_d), "n"(SA));
}

template <int N>
__device__ __forceinline__ void fence_regs(float (&r)[N]) {
#pragma unroll
    for (int i = 0; i < N; ++i) asm volatile("" : "+f"(r[i])::"memory");
}

__device__ __forceinline__ uint32_t bf2_add(uint32_t a, uint32_t b) {
    uint32_t r;
    asm volatile("add.rn.bf16x2 %0, %1, %2;" : "=r"(r) : "r"(a), "r"(b));
    return r;
}
__device__ __forceinline__ uint32_t bf2_sub(uint32_t a, uint32_t b) {
    uint32_t r;
    asm volatile("sub.rn.bf16x2 %0, %1, %2;" : "=r"(r) : "r"(a), "r"(b));
    return r;
}
template <uint32_t B>
__device__ __forceinline__ uint32_t bf2_fma(uint32_t a, uint32_t cc) {
    uint32_t r;
    asm volatile("fma.rn.bf16x2 %0, %1, %2, %3;" : "=r"(r) : "r"(a), "r"(B), "r"(cc));
    return r;
}
__device__ __forceinline__ uint32_t pack_bf16(float a, float b) {
    __nv_bfloat162 v = __floats2bfloat162_rn(a, b);
    return *reinterpret_cast<uint32_t*>(&v);
}

__device__ __forceinline__ uint32_t opaque_add(uint32_t a, uint32_t b) {
    uint32_t r;
    asm volatile("add.u32 %0, %1, %2;" : "=r"(r) : "r"(a), "r"(b));
    return r;
}
template <int K>
__device__ __forceinline__ void make_quads(uint32_t (&q)[12], const uint32_t (&x)[24], const uint32_t (&d2)[24],
                                           const uint32_t (&u)[24], int kc, uint32_t coef = 0) {
    uint32_t e[8];
#pragma unroll
    for (int i = 0; i < 8; ++i) e[i] = K == 1 ? bf2_add(x[kc * 8 + i], d2[kc * 8 + i]) : bf2_sub(x[kc * 8 + i], d2[kc * 8 + i]);
#pragma unroll
    for (int jj = 0; jj < 3; ++jj) {
        const int j = jj == 0 ? 1 : jj == 1 ? 0 : 2;
#pragma unroll
        for (int hl = 0; hl < 2; ++hl) {
#pragma unroll
            for (int h = 0; h < 2; ++h) {
                const int i = ((j + h) >> 1) * 4 + hl * 2 + ((j + h) & 1);
                const uint32_t uu = u[kc * 8 + i];
                if (K < 0) asm volatile("fma.rn.bf16x2 %0, %1, %2, %3;" : "=r"(q[j * 4 + hl * 2 + h]) : "r"(uu), "r"(coef), "r"(e[i]));
                else q[j * 4 + hl * 2 + h] = K == 0 ? bf2_fma<0x3f003f00u>(uu, e[i]) : K == 1 ? bf2_sub(e[i], uu)
                                      : K == 2 ? bf2_fma<0x40404040u>(e[i], uu) : bf2_fma<0xc000c000u>(uu, e[i]);
            }
        }
    }
}
template <bool MAKE_U, bool TIE>
__device__ __forceinline__ void make_mid(uint32_t (&q)[12], uint32_t (&d1)[24], const uint32_t (&d2)[24], uint32_t (&u)[24], int kc,
                                         const uint32_t (&d3)[24], uint32_t wg) {
    uint32_t y[8];
#pragma unroll
    for (int i = 0; i < 8; ++i) {
        y[i] = bf2_sub(d2[kc * 8 + i], d3[kc * 8 + i]);
        if (MAKE_U) asm volatile("sub.rn.bf16x2 %0, %0, %1;" : "+r"(u[kc * 8 + i]) : "r"(d1[kc * 8 + i]));
        if (TIE) asm volatile("{\n\t.reg .pred q;\n\tsetp.ne.u32 q, %3, 7;\n\t@q fma.rn.bf16x2 %0, %0, %2, %1;\n\t}" : "+r"(d1[kc * 8 + i]) : "r"(y[i]), "r"(0x40004000u), "r"(wg));
        else asm volatile("fma.rn.bf16x2 %0, %0, %2, %1;" : "+r"(d1[kc * 8 + i]) : "r"(y[i]), "r"(0x40004000u));
    }
#pragma unroll
    for (int jj = 0; jj < 3; ++jj) {
        const int j = jj == 0 ? 1 : jj == 1 ? 0 : 2;
#pragma unroll
        for (int hl = 0; hl < 2; ++hl) {
#pragma unroll
            for (int h = 0; h < 2; ++h) {
                const int i = ((j + h) >> 1) * 4 + hl * 2 + ((j + h) & 1);
                q[j * 4 + hl * 2 + h] = bf2_fma<0x3fc03fc0u>(y[i], u[kc * 8 + i]);
            }
        }
    }
}

struct Ctx {
    uint32_t bar;
    uint32_t wdesc;
    uint32_t wready, wg, tlo, k, zero, tlo2, vz, ua;
    int rk;
    uint32_t ld0, ld1;
    uint32_t xbuf;
    uint32_t r_off;
};

__device__ __forceinline__ void sb(const Ctx& c) {
    asm volatile("{\n\t.reg .pred q;\n\tsetp.eq.u32 q, %1, 7;\n\t@q mov.u32 %0, %clock;\n\t}" : "+r"(const_cast<Ctx&>(c).vz) : "r"(c.wg) : "memory");
}
__device__ __forceinline__ void sbz(const Ctx& c) {
    asm volatile("{\n\t.reg .pred q;\n\tsetp.eq.u32 q, %1, 7;\n\t@q mov.u32 %0, %clock;\n\t}" : "+r"(const_cast<Ctx&>(c).zero) : "r"(c.wg) : "memory");
}
#define FTW(n)
#define FTM
__device__ __forceinline__ void sbk(Ctx& c) {
    asm volatile("{\n\t.reg .pred q;\n\tsetp.eq.u32 q, %1, 7;\n\t@q mov.u32 %0, %clock;\n\t}" : "+r"(c.k) : "r"(c.wg) : "memory");
}
template <int OFF>
__device__ __forceinline__ void ldsm(uint32_t* r, uint32_t a, uint32_t ua) {
    asm volatile("{\n\t.reg .u32 t;\n\tadd.u32 t, %4, %5;\n\tldmatrix.sync.aligned.m8n8.x4.shared.b16 {%0, %1, %2, %3}, [t + %6];\n\t}"
                 : "=r"(r[0]), "=r"(r[1]), "=r"(r[2]), "=r"(r[3]) : "r"(a), "r"(ua), "n"(OFF) : "memory");
}
template <bool PLUS>
__device__ __forceinline__ uint32_t addr2(uint32_t b, uint32_t t) {
    uint32_t r;
    if (PLUS) asm volatile("mad.lo.s32 %0, %1, 2, %2;" : "=r"(r) : "r"(b), "r"(t));
    else asm volatile("{\n\t.reg .s32 x;\n\tneg.s32 x, %2;\n\tmad.lo.s32 %0, %1, 2, x;\n\t}" : "=r"(r) : "r"(b), "r"(t));
    return r;
}
template <int SLOT, int KC>
__device__ __forceinline__ void ld_chunk_t(uint32_t (&r)[24], const Ctx& c, uint32_t ua, uint32_t ub) {
    if (KC == 2) {
        ldsm<SLOT>(&r[16], c.ld0, ub);
        ldsm<SLOT>(&r[20], c.ld1, ub);
    } else {
        ldsm<2 * SLOT + KC * 16>(&r[KC * 8], addr2<KC == 0>(c.ld0, c.vz), ua);
        ldsm<2 * SLOT + 16 - KC * 16>(&r[KC * 8 + 4], addr2<KC != 0>(c.ld1, c.vz), ua);
    }
}
#define ld_chunk(r, c, slot, kc) ld_chunk_t<slot, kc>(r, c, c.ua, 0)

__device__ __forceinline__ void mma3p(float (&acc)[48], const uint32_t* q0, const uint32_t* q1, const uint32_t* q2,
                                      const Ctx& c, int k, int kc, bool fresh) {
    uint32_t wd;
    asm volatile("mov.b32 %0, %1;" : "=r"(wd) : "r"(c.wdesc));
    wgmma_fence();
#pragma unroll
    for (int j = 0; j < 3; ++j) {
        const uint32_t lo = wd + (uint32_t)((CP(k) * W_COMP + j * W_TAP + (kc == 2 ? 4 - 4 * c.rk : kc + 2 * c.rk) * W_K8) >> 4);
        const uint32_t hi = (uint32_t)((kc == 2 ? W_K8 : 2 * W_K8) >> 4) | (2u << 30);
        uint64_t db;
        asm("mov.b64 %0, {%1, %2};" : "=l"(db) : "r"(lo), "r"(hi));
        if (k == 3 && c.rk == 1) wgmma_m64n96k16<-1>(acc, j == 0 ? q0 : j == 1 ? q1 : q2, db, (fresh && j == 0) ? 0 : 1);
        else wgmma_m64n96k16<1>(acc, j == 0 ? q0 : j == 1 ? q1 : q2, db, (fresh && j == 0) ? 0 : 1);
    }
    wgmma_commit();
}
__device__ __forceinline__ void mma3(float (&acc)[48], const uint32_t (&q)[12], const Ctx& c, int k, int kc, bool fresh) {
    mma3p(acc, &q[0], &q[4], &q[8], c, k, kc, fresh);
}
__device__ __forceinline__ void make_dup(uint32_t (&q)[12], const uint32_t (&u)[24], const Ctx& c, int kc) {
#pragma unroll
    for (int i = 0; i < 4; ++i)
        q[kc * 4 + i] = opaque_add(u[kc * 8 + (i & 1) * 3 + (i >> 1) * 2 + 1], c.zero);
}
__device__ __forceinline__ void mma3d(float (&acc)[48], const uint32_t (&u)[24], const uint32_t (&q)[12], const Ctx& c, int k, int kc, int first = 0) {
    mma3p(acc, &u[kc * 8], &q[kc * 4], &u[kc * 8 + 4], c, k, kc, kc == first);
}
__device__ __forceinline__ void mma3u(float (&acc)[48], const uint32_t (&u)[24], uint32_t (&q)[12], const Ctx& c, int kc) {
    make_dup(q, u, c, kc);
    mma3d(acc, u, q, c, 3, kc);
}

__device__ __forceinline__ uint32_t pack_word(const float (&acc)[48], int i, int m) {
    const int o = ((i % 3) * 4 + m) * 4 + (i / 3) * 2;
    return pack_bf16(acc[o], acc[o + 1]);
}
__device__ __forceinline__ void st_async(uint32_t addr, uint32_t r0, uint32_t r1, uint32_t r2, uint32_t r3, uint32_t rbar) {
    asm volatile("st.async.weak.shared::cluster.mbarrier::complete_tx::bytes.v4.b32 [%0], {%1, %2, %3, %4}, [%5];"
                 ::"r"(addr), "r"(r0), "r"(r1), "r"(r2), "r"(r3), "r"(rbar) : "memory");
}
template <int I0, int I1, int SUB>
__device__ __forceinline__ void send_acc(float (&acc)[48], const Ctx& c, int n = 0) {
    if (I0 >= I1) return;
    fence_regs(acc);
    const uint32_t ro = c.r_off + (c.zero >> n), rx = c.xbuf + ro, rb = c.bar + B_FFULL + ro;
#pragma unroll
    for (int i = I0; i < I1; ++i)
        st_async(rx + ((i - SUB) / 3) * X_UNIT + (i % 3) * X_CH, pack_word(acc, i, 0), pack_word(acc, i, 1), pack_word(acc, i, 2),
                 pack_word(acc, i, 3), rb);
}
template <int I, bool H = true>
__device__ __forceinline__ void send_half(const uint32_t (&p)[12], const Ctx& c, int n = 0) {
    const uint32_t ro = c.r_off + (c.zero >> n), rx = c.xbuf + ro, rb = c.bar + (H ? B_HFULL : B_FFULL) + ro;
    st_async(rx + (H ? 2 * X_UNIT : 0) + I * X_CH, p[I * 4], p[I * 4 + 1], p[I * 4 + 2], p[I * 4 + 3], rb);
}
template <int I0, int N>
__device__ __forceinline__ void fin_pack(float (&acc)[48], uint32_t (&pk)[N * 4]) {
    fence_regs(acc);
#pragma unroll
    for (int i = 0; i < N * 4; ++i) {
        pk[i] = pack_word(acc, I0 + (i >> 2), i & 3);
        asm volatile("" : "+r"(pk[i]));
    }
}
template <int N>
__device__ __forceinline__ void fin_load(uint32_t (&v)[N * 4], const Ctx& c, int off) {
#pragma unroll
    for (int i = 0; i < N; ++i)
        asm volatile("ld.shared.v4.b32 {%0, %1, %2, %3}, [%4];"
                     : "=r"(v[i * 4 + 0]), "=r"(v[i * 4 + 1]), "=r"(v[i * 4 + 2]), "=r"(v[i * 4 + 3])
                     : "r"(c.xbuf + off + (i / 3) * X_UNIT + (i % 3) * X_CH) : "memory");
}
template <int N>
__device__ __forceinline__ void fin_store(uint32_t (&pk)[N * 4], const uint32_t (&v)[N * 4], const Ctx& c, int off, int sbar) {
#pragma unroll
    for (int i = 0; i < N; ++i) {
#pragma unroll
        for (int j = i * 4; j < i * 4 + 4; ++j) asm volatile("add.rn.bf16x2 %0, %0, %1;" : "+r"(pk[j]) : "r"(v[j]));
        asm volatile("st.shared.v4.b32 [%0], {%1, %2, %3, %4};"
                     ::"r"(c.xbuf + off + (i / 3) * X_UNIT + (i % 3) * X_CH), "r"(pk[i * 4]), "r"(pk[i * 4 + 1]), "r"(pk[i * 4 + 2]),
                       "r"(pk[i * 4 + 3]) : "memory");
    }
    if (sbar >= 0) mbar_arrive_warp(c.bar + sbar);
}

__device__ __forceinline__ void pin(const uint32_t* r, const Ctx& c) {
    asm volatile("{\n\t.reg .pred q;\n\tsetp.ne.u32 q, %12, 7;\n\t@q bra.uni PIN_SKIP;\n\t"
                 "st.volatile.shared.v4.b32 [%13], {%0, %1, %2, %3};\n\tst.volatile.shared.v4.b32 [%13], {%4, %5, %6, %7};\n\t"
                 "st.volatile.shared.v4.b32 [%13], {%8, %9, %10, %11};\n\tPIN_SKIP:\n\t}"
                 ::"r"(r[0]), "r"(r[1]), "r"(r[2]), "r"(r[3]), "r"(r[4]), "r"(r[5]), "r"(r[6]), "r"(r[7]), "r"(r[8]), "r"(r[9]),
                   "r"(r[10]), "r"(r[11]), "r"(c.wg), "r"(c.bar) : "memory");
}
__device__ __forceinline__ void pin4(const uint32_t* r, const Ctx& c) {
    asm volatile("{\n\t.reg .pred q;\n\tsetp.eq.u32 q, %4, 7;\n\t@q st.volatile.shared.v4.b32 [%5], {%0, %1, %2, %3};\n\t}"
                 ::"r"(r[0]), "r"(r[1]), "r"(r[2]), "r"(r[3]), "r"(c.wg), "r"(c.bar) : "memory");
}
__device__ __forceinline__ void acc_add(float& d, float x, float k) {
    asm volatile("fma.rn.f32 %0, %1, %2, %0;" : "+f"(d) : "f"(x), "f"(k));
}
__device__ __forceinline__ void acc_scale_add(float& d, float k, float x) {
    asm volatile("fma.rn.f32 %0, %0, %2, %1;" : "+f"(d) : "f"(x), "f"(k));
}
template <int RANK, int I0 = 0, int I1 = 24>
__device__ __forceinline__ void mid_row(float (&b)[48], const float (&k)[48], uint32_t (&ps)[12], uint32_t (&pk)[12],
                                        float f = -2.f) {
#pragma unroll
    for (int i = I0; i < I1; ++i) {
        const int ch = i >> 2, o = ((ch % 3) * 4 + (i & 3)) * 4 + (ch / 3) * 2;
        acc_scale_add(b[o], f, k[o]);
        acc_scale_add(b[o + 1], f, k[o + 1]);
        uint32_t& dst = (i / 12 == RANK) ? pk[i % 12] : ps[i % 12];
        dst = pack_bf16(b[o], b[o + 1]);
        asm volatile("" : "+r"(dst));
    }
}
template <int I0, int I1>
__device__ __forceinline__ void acc_add_n(float (&d)[48], const float (&x)[48], float k) {
#pragma unroll
    for (int i = I0; i < I1; ++i) acc_add(d[i], x[i], k);
}

#define LOCK 1
__device__ __forceinline__ void stagger_lead(const Ctx& c, uint32_t id) {
    if (LOCK) {
        asm volatile("{\n\t.reg .pred p;\n\tsetp.eq.u32 p, %1, 0;\n\t@p bar.sync %0, 256;\n\t}" ::"r"(id), "r"(c.wg) : "memory");
        return;
    }
    asm volatile("{\n\t.reg .pred p;\n\tsetp.eq.u32 p, %1, 0;\n\t@p bar.arrive %0, 256;\n\t}" ::"r"(id), "r"(c.wg) : "memory");
}
__device__ __forceinline__ void stagger_lag(const Ctx& c, uint32_t id) {
    asm volatile("{\n\t.reg .pred p;\n\tsetp.ne.u32 p, %1, 0;\n\t@p bar.sync %0, 256;\n\t}" ::"r"(id), "r"(c.wg) : "memory");
}

#define GAPB 1
#define DEFM 0
#define M1O 0x012
#define M1O0 M1O
#define MO(i) (((RANK == 0 ? M1O0 : M1O) >> (8 - 4 * (i))) & 3)
#define QHW 1
#define CPY 0
#define LDP 0
#define DUPL 0
#define PQ0 0x15
#define PQ1 0x1c
#define TIE0 0
#define TIE1 0
#define WA 0
#define WB 0
#define PKF (AT(23) == PKSLOT)
#define PROBE 0
#define PAPOS 0
#define PPOS 1
#define CS1 24
#define FT_BASE 538
template <int RANK, bool LAST>
__device__ __forceinline__ void phase1b(Ctx& c, float (&accS)[48], float (&accK)[48], float (&accC)[48],
                                        uint32_t (&d0)[24], uint32_t (&d1)[24], const uint32_t (&d2)[24],
                                        const uint32_t (&u)[24], uint32_t (&qd)[12], uint32_t (&qh)[12]) {
    uint32_t pa_ = 0;
    if ((PROBE & 1) && PAPOS == 0) pa_ = mbar_try(c.bar + B_FULLA, LAST ? (NIT - 1) & 1 : c.k & 1);
    fence_regs(accS);
    fence_regs(accC);
#pragma unroll
    for (int i = 0; i < 48; ++i)
        asm volatile("fma.rn.f32 %0, %1, %2, %3;" : "=f"(accK[i]) : "f"(accS[i]), "f"(RANK == 0 ? 1.f / 3.f : -4.f / 3.f), "f"(accC[i]));
    constexpr float CF = RANK == 0 ? -1.f / 6.f : -1.f / 3.f;
    if (DUPL) make_dup(qd, d1, c, MO(0));
    mma3d(accK, d1, qd, c, 1, MO(0), -1);
    sb(c);
    if ((PROBE & 1) && PAPOS == 1) pa_ = mbar_try(c.bar + B_FULLA, LAST ? (NIT - 1) & 1 : c.k & 1);
    if (!LAST && LEADPOS == 12) stagger_lead(c, c.k + 1);
    make_dup(qd, d1, c, MO(1));
    mma3d(accK, d1, qd, c, 1, MO(1), -1);
    sb(c);
    if ((PROBE & 1) && PAPOS == 2) pa_ = mbar_try(c.bar + B_FULLA, LAST ? (NIT - 1) & 1 : c.k & 1);
    if (!LAST && LEADPOS == 13) stagger_lead(c, c.k + 1);
    acc_add_n<0, CS1>(accC, accS, CF);
    if (PROBE & 16) sb(c);
    if (__builtin_expect(!pa_, PROBE & 1 ? 0 : 1)) mbar_wait(c.bar + B_FULLA, LAST ? (NIT - 1) & 1 : c.k & 1);
    if (WA == 1 && !LAST && c.k == 0) mbar_wait(c.bar + B_FULLA, 0);
    if (WA) sb(c);
    wgmma_wait<1>();
    if (LDP == 1) sb(c);
    if (LDP < 2) {
        if (RANK == 0 && !LAST) ld_chunk(d1, c, SL4, 0);
        else ld_chunk(d0, c, SL0, 0);
    }
    make_dup(qd, d1, c, MO(2));
    mma3d(accK, d1, qd, c, 1, MO(2), -1);
    sb(c);
    if (!LAST && LEADPOS == 14) stagger_lead(c, c.k + 1);
    if (LDP == 2) {
        if (RANK == 0 && !LAST) ld_chunk(d1, c, SL4, 0);
        else ld_chunk(d0, c, SL0, 0);
    }
    acc_add_n<CS1, 48>(accC, accS, CF);
    sb(c);
    wgmma_wait<QHW>();
    if (LDP == 3) {
        if (RANK == 0 && !LAST) ld_chunk(d1, c, SL4, 0);
        else ld_chunk(d0, c, SL0, 0);
    }
    if (RANK == 0 && !LAST) make_quads<4>(qh, d1, d2, u, 0);
    else make_quads<0>(qh, d0, d2, u, 0);
    sb(c);
}

template <int RANK>
__device__ __forceinline__ void consumer(Ctx& c) {
    float accS[48], accK[48], accC[48];
    uint32_t d0[24], d1[24], d2[24], u[24];
    uint32_t qd[12];
#pragma unroll
    for (int i = 0; i < 48; ++i) { accS[i] = 0.f; accC[i] = 0.f; }
    {
        uint32_t qa[12], qe[12];
        mbar_wait(c.bar + B_FULL0, 0);
        c.rk = RANK;
        sbz(c);
        const uint32_t xo = (uint32_t)(OFF_X - OFF_IN) - c.wg * (4 * IN_ROW - X_BYTES);
        ld_chunk_t<0, 0>(d1, c, c.ua + xo, 0);
        ld_chunk(u, c, SL3, 0);
        ld_chunk_t<0, 1>(d1, c, c.ua + xo, 0);
        ld_chunk(u, c, SL3, 1);
        ld_chunk_t<0, 2>(d1, c, 0, xo + 2 * IN_SLAB - IN_B);
        ld_chunk(u, c, SL3, 2);
#pragma unroll
        for (int i = 0; i < 24; ++i) u[i] = bf2_sub(u[i], d1[i]);
#pragma unroll
        for (int kc = 0; kc < 3; ++kc) make_dup(qe, u, c, kc);
        TL(18);
        mbar_wait(c.wready, 0);
        TL(19);
#pragma unroll
        for (int kc = 0; kc < 3; ++kc) mma3d(accS, u, qe, c, 3, kc);
        mbar_wait(c.bar + B_FULLC, 0);
        ld_chunk(d2, c, SL2, 0);
        ld_chunk(d0, c, SL3, 0);
        ld_chunk(d2, c, SL2, 1);
        ld_chunk(d0, c, SL3, 1);
#pragma unroll
        for (int kc = 0; kc < 3; ++kc) {
            if (kc == 1) { sb(c); ld_chunk(d2, c, SL2, 2); ld_chunk(d0, c, SL3, 2); }
#pragma unroll
            for (int i = kc * 8; i < kc * 8 + 8; ++i) {
                asm volatile("sub.rn.bf16x2 %0, %1, %0;" : "+r"(d0[i]) : "r"(d2[i]));
                asm volatile("fma.rn.bf16x2 %0, %0, %2, %1;" : "+r"(d1[i]) : "r"(d0[i]), "r"(0x40004000u));
                asm volatile("fma.rn.bf16x2 %0, %0, %2, %1;" : "+r"(d0[i]) : "r"(u[i]), "r"(0x3fc03fc0u));
            }
            make_dup(qa, d0, c, kc);
            mma3d(accC, d0, qa, c, 2, kc);
        }
        mbar_arrive_warp(c.bar + B_EMPTYB);
        if (!DUPL) make_dup(qd, d1, c, MO(0));
        if (LAGK == 2) asm volatile("{\n\t.reg .pred p;\n\tsetp.ne.u32 p, %0, 0;\n\t@p bar.arrive 1, 256;\n\t}" ::"r"(c.wg) : "memory");
        if (WA == 2) mbar_wait(c.bar + B_FULLA, 0);
        wgmma_wait<0>();
        c.k = c.zero;
        TL(23);
    }
    constexpr int KA = RANK == 0 ? 4 : 0, KB = 4 - KA;
    constexpr int SA = RANK == 0 ? SL4 : SL0, SB = RANK == 0 ? SL0 : SL4;
    uint32_t (&ea)[24] = RANK == 0 ? d1 : d0;
    uint32_t (&eb)[24] = RANK == 0 ? d0 : d1;
#pragma unroll 1
    while (c.k < NIT - 1) {
#define par(n) ((c.k + (c.zero >> n)) & 1)
        uint32_t qa[12], qb[12], qe[12], qh[12], hs[12], hk[12];
        uint32_t hv[12], pa[12], pb[12], va[12], vb[12], pb_ = 0, ph_ = 0, pf_ = 0;
        phase1b<RANK, false>(c, accS, accK, accC, d0, d1, d2, u, qd, qh);
#define AT(i) (int)(((RANK == 0 ? (i < 16 ? PLA0 : PLB0) : (i < 16 ? PLA1 : PLB1)) >> (60 - 4 * (i & 15))) & 15)
#define SLOT(n)                                                                                   \
        if (AT(2) == n && FMODE != 1) mbar_wait(c.bar + B_FULL0 + FMODE * 8, par(n));             \
        if (PPOS == 0) { PROBES(n) } if (AT(5) == n && __builtin_expect(!pb_, PROBE & 2 ? 0 : 1)) mbar_wait(c.bar + B_FULLB, par(n));                         \
        if (AT(14) == n && __builtin_expect(!ph_, PROBE & 4 ? 0 : 1)) mbar_wait(c.bar + B_HFULL, par(n));                                      \
        if (AT(22) == n && __builtin_expect(!pf_, PROBE & 8 ? 0 : 1)) mbar_wait(c.bar + B_FFULL, par(n));                                      \
        if (n == 2) mbar_arrive_warp(c.bar + B_EMPTYE);                                           \
        if (n == 5) mbar_arrive_warp(c.bar + B_EMPTYF);                                           \
        if (n == EBSLOT) mbar_arrive_warp(c.bar + B_EMPTYB);                                      \
        if (!LLATE(n)) { LOADS(n) }                                                               \
        if (!LATE(n)) { STORES(n) }                                                               \
        if (PPOS == 1) { PROBES(n) }
#define PROBES(n)                                                                                 \
        if ((PROBE & 2) && AT(5) == n + 1) pb_ = mbar_try(c.bar + B_FULLB, par(n));              \
        if ((PROBE & 4) && AT(14) == n + 1) ph_ = mbar_try(c.bar + B_HFULL, par(n));              \
        if ((PROBE & 8) && AT(22) == n + 1) pf_ = mbar_try(c.bar + B_FFULL, par(n));
#define LOADS(n)                                                                                  \
        if (AT(0) == n) ld_chunk(ea, c, SA, 1);                                                   \
        if (AT(1) == n) ld_chunk(ea, c, SA, 2);                                                   \
        if (AT(2) == n) ld_chunk(eb, c, SB, 0);                                                   \
        if (AT(3) == n) ld_chunk(eb, c, SB, 1);                                                   \
        if (AT(4) == n) ld_chunk(eb, c, SB, 2);                                                   \
        if (AT(5) == n) ld_chunk(u, c, SL3, 0);                                                   \
        if (AT(6) == n) ld_chunk(d2, c, SL2, 0);                                                  \
        if (AT(7) == n) ld_chunk(u, c, SL3, 1);                                                   \
        if (AT(8) == n) ld_chunk(d2, c, SL2, 1);                                                  \
        if (AT(9) == n) ld_chunk(u, c, SL3, 2);                                                   \
        if (AT(10) == n) ld_chunk(d2, c, SL2, 2);                                                 \
        if (AT(14) == n) fin_load<3>(hv, c, 2 * X_UNIT);                                          \
        if (AT(22) == n) fin_load<3>(va, c, 0);                                                   \
        if (AT(24) == n) fin_load<3>(vb, c, X_UNIT);
#define STORES(n)                                                                                 \
        if (n == PKSLOT && PKF) { fin_pack<0, 3>(accK, pa); fin_pack<3, 3>(accK, pb); if (AT(23) != n) pin(pa, c); if (AT(25) != n) pin(pb, c); } \
        if (AT(15) == n) fin_store<3>(hk, hv, c, 2 * X_UNIT, B_SH);                               \
        if (AT(23) == n) fin_store<3>(pa, va, c, 0, -1);                                          \
        if (AT(25) == n) fin_store<3>(pb, vb, c, X_UNIT, B_SF);                                   \
        if (LLATE(n) && !LLATE2(n)) { LOADS(n) }                                                  \
        if (AT(11) == n) send_half<0>(hs, c, n);                                                  \
        if (AT(12) == n) send_half<1>(hs, c, n);                                                  \
        if (AT(13) == n) send_half<2>(hs, c, n);                                                  \
        if (AT(16) == n) send_acc<0, 1, 0>(accS, c, n);                                           \
        if (AT(17) == n) send_acc<3, 4, 0>(accS, c, n);                                           \
        if (AT(18) == n) send_acc<1, 2, 0>(accS, c, n);                                           \
        if (AT(19) == n) send_acc<4, 5, 0>(accS, c, n);                                           \
        if (AT(20) == n) send_acc<2, 3, 0>(accS, c, n);                                           \
        if (AT(21) == n) send_acc<5, 6, 0>(accS, c, n);                                           \
        if (LLATE(n) && LLATE2(n)) { LOADS(n) }                                                   \
        if (n == PKSLOT && !PKF) { fin_pack<0, 3>(accK, pa); fin_pack<3, 3>(accK, pb); pin(pa, c); pin(pb, c); }
#define QW(n, Q)                                                                     \
        if (LATE(n)) { Q; sb(c); STORES(n); sb(c); wgmma_wait<1 + NW(n)>(); FTW(n); }        \
        else if (EQ(n)) { Q; sb(c); wgmma_wait<1 + NW(n)>(); FTW(n); } else { sb(c); wgmma_wait<1 + NW(n)>(); FTW(n); Q; } \
        if (PPOS == 2) { PROBES(n) }                                                              \
        if (LAGPOS == n) stagger_lag(c, c.k + LAGK);                                              \
        if (LEADPOS == n) stagger_lead(c, c.k + 1);
#define P1(g, q)                                                                                  \
        SLOT(g + 5);                                                                              \
        if (PG(g) < 4) {                                                                          \
            QW(g + 5, (make_mid<true, (((RANK == 0 ? TIE0 : TIE1) >> (PG(g) & 3)) & 1) != 0>(q, d1, d2, u, PG(g) & 3, u, c.wg)));                                 \
            mma3(accC, q, c, 2, PG(g) & 3, g == 0);                                               \
        } else {                                                                                  \
            QW(g + 5, make_dup(qe, u, c, PG(g) & 3));                                             \
            mma3d(accS, u, qe, c, 3, PG(g) & 3, M1FIRST);                                         \
        }
        if (!GAPB) {
            wgmma_wait<0>();
            fence_regs(accK);
            if (!DEFM) {
                mid_row<RANK>(accC, accK, hs, hk);
                pin(hk, c);
                SLOT(15);
            } else {
                LOADS(15);
            }
            sbk(c);
            acc_add_n<0, 48>(accS, accK, 1.f);
            mma3(accS, qh, c, KA, 0, false);
            sb(c);
            if (DEFM) {
                mid_row<RANK>(accC, accK, hs, hk);
                pin(hk, c);
                STORES(15);
                sb(c);
            }
        } else {
            mma3(accS, qh, c, KA, 0, false);
            wgmma_wait<1>();
            fence_regs(accK);
            LOADS(15);
            sbk(c);
            mid_row<RANK>(accC, accK, hs, hk);
            pin(hk, c);
            STORES(15);
            sb(c);
        }
        SLOT(0);
        make_quads<KA>(qa, ea, d2, u, 1);
        mma3(accS, qa, c, KA, 1, false);
        sb(c);
        SLOT(1);
        QW(1, make_quads<KA>(qb, ea, d2, u, 2));
        mma3(accS, qb, c, KA, 2, false);
        sb(c);
        SLOT(2);
        QW(2, make_quads<KB>(qa, eb, d2, u, 0));
        if (WB) mbar_wait(c.bar + B_FULLB, par(2));
        if (WB == 2) mbar_wait(c.bar + B_HFULL, par(2));
        if (GAPB) {
            wgmma_wait<0>();
            fence_regs(accS);
            acc_add_n<0, 48>(accS, accK, 1.f);
        }
        mma3(accK, qa, c, KB, 0, false);
        sb(c);
        SLOT(3);
        QW(3, make_quads<KB>(qb, eb, d2, u, 1));
        mma3(accK, qb, c, KB, 1, false);
        sb(c);
        SLOT(4);
        QW(4, make_quads<KB>(qa, eb, d2, u, 2));
        mma3(accK, qa, c, KB, 2, false);
        sb(c);
        P1(0, qb);

        sb(c);
        P1(1, qa);

        sb(c);
        P1(2, qb);

        sb(c);
        P1(3, qa);

        sb(c);
        P1(4, qb);

        sb(c);
        P1(5, qa);

        sb(c);
        SLOT(11);
        if (LAGPOS == 11) stagger_lag(c, c.k + LAGK);
        if (LEADPOS == 11) stagger_lead(c, c.k + 1);
        if (!DUPL) make_dup(qd, d1, c, MO(0));
#pragma unroll
        for (int i = 0; i < 12; ++i)
            if (((RANK == 0 ? PQ0 : PQ1) >> i) & 1) pin4(&d2[(i % 6) * 4], c);
        sbz(c);
        ++c.k;
        if (WA) mbar_wait(c.bar + B_FULLA, c.k & 1);
        wgmma_wait<0>();
        TL(1 + c.k);
#undef par
    }
    {
        constexpr uint32_t par = (NIT - 1) & 1;
        uint32_t qa[12], qb[12], qh[12], hs[12], hk[12], v[12];
        constexpr int S0 = 12 - 12 * RANK, K0 = 12 * RANK;
        uint32_t pk[12];
        if (LAGK == 2) stagger_lead(c, NIT);
        phase1b<RANK, true>(c, accS, accK, accC, d0, d1, d2, u, qd, qh);
        mma3(accS, qh, c, 0, 0, RANK == 0);
        wgmma_wait<1>();
        ld_chunk(d0, c, SL0, 1);
        ld_chunk(d0, c, SL0, 2);
        fence_regs(accK);
        mid_row<RANK, S0, S0 + 12>(accC, accK, hs, hk);
        send_half<0>(hs, c);
        send_half<1>(hs, c);
        send_half<2>(hs, c);
        sb(c);
        make_quads<0>(qa, d0, d2, u, 1);
        mma3(accS, qa, c, 0, 1, false);
        make_quads<0>(qb, d0, d2, u, 2);
        mma3(accS, qb, c, 0, 2, false);
        mid_row<RANK, K0, K0 + 12>(accC, accK, hs, hk);
        mbar_wait(c.bar + B_FULLB, par);
        wgmma_wait<0>();
        fence_regs(accS);
        mid_row<RANK, S0, S0 + 12>(accS, accK, hs, pk, 1.f);
        send_half<0, false>(hs, c);
        send_half<1, false>(hs, c);
        send_half<2, false>(hs, c);
        mbar_wait(c.bar + B_HFULL, par);
        fin_load<3>(v, c, 2 * X_UNIT);
        mid_row<RANK, K0, K0 + 12>(accS, accK, hs, pk, 1.f);
        fin_store<3>(hk, v, c, 2 * X_UNIT, B_SH);
        mbar_wait(c.bar + B_FFULL + c.zero, par);
        fin_load<3>(v, c, 0);
        fin_store<3>(pk, v, c, 0, B_SF);
        TL(17);
    }
}

__device__ __forceinline__ void wt_load(uint32_t (&g)[36], uint32_t unit, int lane) {
    const uint32_t src = unit + (lane >> 2) * 192 + ((lane & 3) << 4);
#pragma unroll
    for (int i = 0; i < 9; ++i)
        asm volatile("ld.shared.v4.b32 {%0, %1, %2, %3}, [%4];"
                     : "=r"(g[i * 4]), "=r"(g[i * 4 + 1]), "=r"(g[i * 4 + 2]), "=r"(g[i * 4 + 3])
                     : "r"(src + (i / 3) * 64 + (i % 3) * 2 * W_COMP) : "memory");
}
__device__ __forceinline__ void stsm(uint32_t addr, const uint32_t* v) {
    asm volatile("stmatrix.sync.aligned.m8n8.x4.shared.b16 [%0], {%1, %2, %3, %4};"
                 ::"r"(addr), "r"(v[0]), "r"(v[1]), "r"(v[2]), "r"(v[3]) : "memory");
}
template <int PART>
__device__ __forceinline__ void wt_store(const uint32_t (&g)[36], uint32_t unit, int lane) {
    const uint32_t dst = unit + (lane & 7) * 64 + ((((lane >> 3) ^ (lane >> 1)) & 3) << 4);
    __syncwarp();
#pragma unroll
    for (int r = 0; r < 3; ++r) {
        const uint32_t *a = &g[r * 12], *b = a + 4, *cc = a + 8;
        uint32_t u1[4], u2[4], u3[4];
#pragma unroll
        for (int i = 0; i < 4; ++i) {
            uint32_t h;
            asm("add.rn.bf16x2 %0, %1, %2;" : "=r"(h) : "r"(a[i]), "r"(cc[i]));
            asm("mul.rn.bf16x2 %0, %1, %2;" : "=r"(h) : "r"(h), "r"(0x3f003f00u));
            asm("fma.rn.bf16x2 %0, %1, %2, %3;" : "=r"(u1[i]) : "r"(b[i]), "r"(0x3f003f00u), "r"(h));
            asm("fma.rn.bf16x2 %0, %1, %2, %3;" : "=r"(u2[i]) : "r"(b[i]), "r"(0xbf00bf00u), "r"(h));
            asm("mul.rn.bf16x2 %0, %1, %2;" : "=r"(h) : "r"(u2[i]), "r"(0xbaabbaabu));
            asm("fma.rn.bf16x2 %0, %0, %1, %2;" : "+r"(u2[i]) : "r"(0x3f2b3f2bu), "r"(h));
            asm("fma.rn.bf16x2 %0, %1, %2, %3;" : "=r"(h) : "r"(a[i]), "r"(0x3e803e80u), "r"(cc[i]));
            asm("fma.rn.bf16x2 %0, %1, %2, %3;" : "=r"(u3[i]) : "r"(h), "r"(0x40004000u), "r"(b[i]));
        }
        if (PART & 1) {
            stsm(dst + r * 512 + CP(2) * W_COMP, u2);
            stsm(dst + r * 512 + CP(1) * W_COMP, u1);
            stsm(dst + r * 512 + CP(3) * W_COMP, u3);
        }
        if (PART & 2) {
            stsm(dst + r * 512 + CP(0) * W_COMP, a);
            stsm(dst + r * 512 + CP(4) * W_COMP, cc);
        }
    }
}

__device__ __forceinline__ int seq_row(int seg, int row_par, int n) {
    const int q = (seg & 1) ? seg * SEG - 1 + n : seg * SEG + SEG - n;
    return 2 * q + row_par;
}

struct XMaps { CUtensorMap m[2]; };
#define xmap xm.m[0]
__global__ void __cluster_dims__(2, 1, 1) __launch_bounds__(384, 1)
conv_kernel(const __grid_constant__ XMaps xm, const __grid_constant__ CUtensorMap omap,
            const char* __restrict__ wp, const char* __restrict__ xp) {
    extern __shared__ uint8_t smem_raw[];
    const uint32_t base = (smem_u32(smem_raw) + 1023u) & ~1023u;
    const uint32_t wbase = base + OFF_W;
    const uint32_t bar_base = base + OFF_BAR;
    const uint32_t wbar_b = bar_base + 256, wready_b = bar_base + 280;

    const int tid = threadIdx.x;
    const int warp = tid >> 5, lane = tid & 31;
    const int rank = blockIdx.x & 1;
    const int cluster = blockIdx.x >> 1;
    const int strip = cluster & 7, seg = cluster >> 3;
    const int fmode = rank ? FMODE1 : FMODE0;
    uint32_t c_start;
    asm volatile("mov.u32 %0, %clock;" : "=r"(c_start) :: "memory");

    const int uwarp = __shfl_sync(0xffffffffu, warp, 0);
    const bool el = elect();
#define PFW 3
#define PFBLK                                                                                                \
    if (uwarp == PFW) {                                                                                      \
        if (lane < 20) {                                                                                     \
            const char* p = wp + (size_t)(((blockIdx.x & 63) * 20 + lane + (blockIdx.x >> 6) * 16) * 128);   \
            asm volatile("prefetch.global.L2 [%0];" ::"l"(p) : "memory");                                    \
        }                                                                                                    \
    }
#define PFPOS 0
    if (PFPOS == 0) { PFBLK }
    if (uwarp == 0 && el) {
        for (int i = 0; i < 3; ++i) mbar_init(wbar_b + i * 8, 1);
        asm volatile("fence.proxy.async.shared::cta;" ::: "memory");
        const int up = (seg & 1) ^ 1;
#pragma unroll
        for (int j = 0; j < 3; ++j) {
#pragma unroll
            for (int i = 0; i < 3; ++i)
                asm volatile("cp.async.bulk.shared::cluster.global.mbarrier::complete_tx::bytes [%0], [%1], %2, [%3];"
                             ::"r"(wbase + ((up ? 2 - i : i) * 6 + j) * W_TAP), "l"(wp + (2 * (i * 3 + j) + rank) * W_TAP),
                               "r"(W_TAP), "r"(wbar_b + j * 8) : "memory");
        }
        for (int j = 0; j < 3; ++j) mbar_expect_tx(wbar_b + j * 8, 3 * W_TAP);
        asm volatile("fence.mbarrier_init.release.cluster;" ::: "memory");
    }
    if (PFPOS == 1) { PFBLK }
#define RT 320
    if (uwarp == 2 && el) {
        for (int i = 0; i < 2; ++i) {
            mbar_init(bar_base + i * 128 + B_FULLA, 3);
            mbar_init(bar_base + i * 128 + B_FULLB, 2);
            mbar_init(bar_base + i * 128 + B_EMPTYE, 4);
            mbar_init(bar_base + i * 128 + B_EMPTYF, 4);
            mbar_init(bar_base + i * 128 + B_EMPTYB, 4);
            mbar_init(bar_base + i * 128 + B_HFULL, 1);
            mbar_init(bar_base + i * 128 + B_FFULL, 1);
            mbar_init(bar_base + i * 128 + B_SH, 4);
            mbar_init(bar_base + i * 128 + B_SF, 4);
            mbar_expect_tx(bar_base + i * 128 + B_HFULL, X_TX);
            mbar_expect_tx(bar_base + i * 128 + B_FFULL, 2 * X_TX);
            mbar_arrive(bar_base + i * 128 + B_FULLA);
            mbar_arrive(bar_base + i * 128 + B_FULLB);
        }
        mbar_init(wready_b, 10);
        asm volatile("fence.mbarrier_init.release.cluster;" ::: "memory");
        asm volatile("fence.proxy.async.shared::cta;" ::: "memory");
    }
    if (uwarp == 10 && el) {
        asm volatile("prefetch.tensormap [%0];" ::"l"((uint64_t)(&xmap)) : "memory");
        asm volatile("prefetch.tensormap [%0];" ::"l"((uint64_t)(&xmap + 1)) : "memory");
        for (int i = 0; i < 4; ++i) mbar_init(bar_base + (i >> 1) * 128 + (i & 1) * B_FULLC, 1);
        for (int i = 0; i < 4; ++i) mbar_expect_tx(bar_base + (i >> 1) * 128 + (i & 1) * B_FULLC, (2 - (i & 1)) * IN_ROW);
        asm volatile("fence.mbarrier_init.release.cluster;" ::: "memory");
        asm volatile("fence.proxy.async.shared::cta;" ::: "memory");
    }
    __syncwarp();
    asm volatile("barrier.cluster.arrive.relaxed.aligned;" ::: "memory");
#define RSTEP 150
    if (uwarp == 10 && el) {
#pragma unroll
        for (int i = 0; i < 6; ++i) {
            const int wg = (RORD >> (i * 4 + 2)) & 1, n = (RORD >> (i * 4)) & 3;
            const uint32_t fb = bar_base + wg * 128 + (n == 2 ? B_FULLC : B_FULL0);
            if (i == 0 || RSTEP) while ((uint32_t)clock() - c_start < ROW_DELAY + i * RSTEP) {}
            const uint32_t dst = base + (n == 1 ? OFF_X + wg * X_BYTES : OFF_IN + wg * 4 * IN_ROW + n * 2 * IN_SLAB);
            load_row(dst, dst + (n == 1 ? 2 * IN_SLAB : IN_B - n * IN_SLAB), &xmap, fb, rank, strip, seq_row(seg, wg, n), true);
        }
    }
    __syncwarp();
#define ST(j)
    ST(0);
    asm volatile("barrier.cluster.wait.aligned;" ::: "memory");
#define WX 4
#define HW0 11
#define HW1 9
    if (uwarp < 8 || uwarp == HW0 || uwarp == HW1) {
        uint32_t ga[36], gb[36];
        const int uw = uwarp < 8 ? uwarp ^ WX : uwarp == HW0 ? 8 : 9;
        const uint32_t unit = wbase + uw * W_K8;
        ST(1);
        if (uw < 8) {
            mbar_wait(wbar_b + (uw < 6 ? 0 : 8), 0);
            ST(2);
            wt_load(ga, unit, lane);
        }
        mbar_wait(wbar_b + (uw < 4 ? 8 : 16), 0);
        ST(3);
        wt_load(gb, unit + 8 * W_K8, lane);
        if (uw < 8) wt_store<3>(ga, unit, lane);
        ST(4);
        wt_store<3>(gb, unit + 8 * W_K8, lane);
        ST(5);
        asm volatile("fence.proxy.async.shared::cta;" ::: "memory");
        mbar_arrive_warp(wready_b);
        ST(6);
    }

    if (uwarp >= 8) {
        asm volatile("setmaxnreg.dec.sync.aligned.u32 24;");
        {
            const int wg = uwarp & 1;
            const uint32_t bar = bar_base + wg * 128;
            const int step = (seg & 1) ? 2 : -2;
            if (uwarp < 10) {
                const uint32_t in = base + OFF_IN + wg * 4 * IN_ROW;
                const char* pf = xp + (strip * 64 + rank * 32) * 192;
                int row = seq_row(seg, wg, 0);
#pragma unroll 1
                for (int t = 0; t < NIT; ++t, row += 3 * step) {
#pragma unroll
                    for (int g = 0; g < 3; ++g) {
                        const int sl = g == 2 ? 2 : (g ^ rank ^ 1);
                        const uint32_t fb = bar + (g == 2 ? B_FULLB : B_FULLA);
                        mbar_wait_h(bar + B_EMPTYE + g * 8, t & 1);
                        STAMP(t, 6 + g);
                        if (el) {
                            const bool ld = t < NIT - 1 || sl == 0;
                            if (ld) {
                                if (g == 2) load_row(in + 2 * SL3, in + IN_B + SL3, &xmap, fb, rank, strip, row + 6 * step, true);
                                load_row(in + sl * 2 * IN_SLAB, in + IN_B + sl * IN_SLAB, &xmap, fb, rank, strip, row + (g == 2 ? 5 : 4 * sl) * step, true);
                            }
                            mbar_expect_tx(fb, ld ? (g == 2 ? 2 * IN_ROW : IN_ROW) : 0);
                            const int n = 3 * t + g + 1, prow = row + (g + 1 + PF) * step;
                            if (n >= PF0 && n + PF < SEG + 2 && (unsigned)prow < IMG_H)
                            {
                                asm volatile("cp.async.bulk.prefetch.L2.global [%0], %1;"
                                             ::"l"(pf + (size_t)prow * (IMG_W * 192)), "r"(32 * 192) : "memory");
                            }
                        }
                        __syncwarp();
                        if (g) STAMP(t, 8 + g);
                    }
                }
            } else {
                const uint32_t src = base + OFF_X + wg * X_BYTES;
                const uint32_t r_bar = mapa(bar, rank ^ 1);
                if (wg == 0 && lane < 4)
                    asm volatile("mbarrier.arrive.shared::cta.b64 _, [%0], 4;" ::"r"(bar + (lane >> 1) * 128 + B_EMPTYE + (lane & 1) * 8) : "memory");
                __syncwarp();
                int row = seq_row(seg, wg, 1);
#pragma unroll 1
                for (int t = 0; t < NIT; ++t, row += 3 * step) {
                    const bool last = t == NIT - 1;
                    mbar_wait_h(bar + B_SH, t & 1);
                    STAMP(t, 0);
                    if (el) {
                        asm volatile("fence.proxy.async.shared::cta;" ::: "memory");
                        tma_store_4d(&omap, src + 2 * X_UNIT, 0, strip * 16, rank, row + step, EF(t, 2));
                        asm volatile("cp.async.bulk.commit_group;" ::: "memory");
                        if (!last) {
                            mbar_expect_tx(bar + B_HFULL, X_TX);
                            asm volatile("cp.async.bulk.wait_group.read 0;" ::: "memory");
                            mbar_arrive_remote(r_bar + B_FULLA);
                        }
                    }
                    __syncwarp();
                    STAMP(t, 1);
                    mbar_wait_h(bar + B_SF, t & 1);
                    STAMP(t, 2);
                    if (el) {
                        asm volatile("fence.proxy.async.shared::cta;" ::: "memory");
                        const int orow = row + (last ? 0 : 2 * rank * step);
                        tma_store_4d(&omap, src, 0, strip * 16, last ? rank : 0, orow, EF(t, 0));
                        if (!last) tma_store_4d(&omap, src + X_UNIT, 0, strip * 16, 1, orow, EF(t, 1));
                        asm volatile("cp.async.bulk.commit_group;" ::: "memory");
                        if (!last) mbar_expect_tx(bar + B_FFULL, t == NIT - 2 ? X_TX : 2 * X_TX);
                        asm volatile("cp.async.bulk.wait_group.read 0;" ::: "memory");
                        if (!last) mbar_arrive_remote(r_bar + B_FULLB);
                    }
                    __syncwarp();
                    STAMP(t, 3);
                }
            }
        }
    } else {
        const int wg = uwarp >> 2;
        const int w4 = warp & 3;
        if (RT >= 256) asm volatile("setmaxnreg.inc.sync.aligned.u32 240;");
        ST(7);
        Ctx c;
        c.bar = bar_base + wg * 128;
        c.wdesc = ((wbase & 0x3FFFF) >> 4) | ((uint32_t)(512 >> 4) << 16);
        c.wready = wready_b;
        c.wg = wg;
        c.k = ~0u;
        c.zero = 0;
        c.tlo2 = bar_base + 576 - bar_base * 4;
        c.tlo = 320;
        {
            const int m = lane >> 3, gg = lane & 7, hl = m >> 1;
            const int rho0 = (m & 1) ? (8 * w4 + gg + 2) : (36 + 8 * w4 + gg);
            const int rho1 = rho0 + 2;
            const uint32_t in = base + OFF_IN + wg * 4 * IN_ROW;
            c.ld0 = in + IN_B + rho0 * 32 + ((hl ^ ((rho0 >> 2) & 1)) << 4);
            c.ld1 = in + IN_B + rho1 * 32 + ((hl ^ ((rho1 >> 2) & 1)) << 4);
            c.vz = (rho0 & 2) << 3;
            c.ua = in - 2 * (in + IN_B);
        }
        c.xbuf = base + OFF_X + wg * X_BYTES + (tid & 127) * 16;
        c.r_off = mapa(c.bar, rank ^ 1) - c.bar;
        c.ld0 = __shfl_sync(0xffffffffu, c.ld0, lane);
        c.ld1 = __shfl_sync(0xffffffffu, c.ld1, lane);
        c.xbuf = __shfl_sync(0xffffffffu, c.xbuf, lane);
        TL(1);
        TLC(20);
        if (rank == 0) consumer<0>(c);
        else consumer<1>(c);
        TLC(21);
    }
}

typedef CUresult (*EncodeFn)(CUtensorMap*, CUtensorMapDataType, cuuint32_t, void*, const cuuint64_t*,
                             const cuuint64_t*, const cuuint32_t*, const cuuint32_t*, CUtensorMapInterleave,
                             CUtensorMapSwizzle, CUtensorMapL2promotion, CUtensorMapFloatOOBfill);

}

extern "C" void kernel_launch(void* const* d_in, const int* in_sizes, int n_in, void* d_out, int out_size) {
    (void)in_sizes; (void)n_in; (void)out_size;
    static EncodeFn encode = nullptr;
    if (!encode) {
        void* fn = nullptr;
        cudaDriverEntryPointQueryResult qres;
        cudaGetDriverEntryPoint("cuTensorMapEncodeTiled", &fn, cudaEnableDefault, &qres);
        encode = (EncodeFn)fn;
        cudaFuncSetAttribute(conv_kernel, cudaFuncAttributeMaxDynamicSharedMemorySize, SMEM_BYTES);
    }
    XMaps xm;
    CUtensorMap omap;
    cuuint32_t estr5[5] = {1, 1, 1, 1, 1};
    {
        cuuint64_t dims[5] = {(cuuint64_t)CH, 2, (cuuint64_t)IMG_W / 4, 2, (cuuint64_t)IMG_H};
        cuuint64_t strides[4] = {(cuuint64_t)CH * 2, (cuuint64_t)CH * 2 * 4, (cuuint64_t)CH * 2 * 2,
                                 (cuuint64_t)IMG_W * CH * 2};
        cuuint32_t box[5] = {16, 2, 18, 2, 1};
        encode(&xmap, CU_TENSOR_MAP_DATA_TYPE_BFLOAT16, 5, d_in[0], dims, strides, box, estr5,
               CU_TENSOR_MAP_INTERLEAVE_NONE, CU_TENSOR_MAP_SWIZZLE_32B, PROMO,
               CU_TENSOR_MAP_FLOAT_OOB_FILL_NONE);
        box[0] = 32;
        encode(&xm.m[1], CU_TENSOR_MAP_DATA_TYPE_BFLOAT16, 5, d_in[0], dims, strides, box, estr5,
               CU_TENSOR_MAP_INTERLEAVE_NONE, CU_TENSOR_MAP_SWIZZLE_64B, PROMO,
               CU_TENSOR_MAP_FLOAT_OOB_FILL_NONE);
    }
    {
        cuuint64_t dims[5] = {32, 2, (cuuint64_t)IMG_H * IMG_W / 4, 3, 2};
        cuuint64_t strides[4] = {(cuuint64_t)CH * 2, (cuuint64_t)CH * 2 * 4, 64, (cuuint64_t)CH * 2 * 2};
        cuuint32_t box[5] = {32, 2, 16, 3, 1};
        encode(&omap, CU_TENSOR_MAP_DATA_TYPE_BFLOAT16, 5, d_out, dims, strides, box, estr5,
               CU_TENSOR_MAP_INTERLEAVE_NONE, CU_TENSOR_MAP_SWIZZLE_NONE, CU_TENSOR_MAP_L2_PROMOTION_NONE,
               CU_TENSOR_MAP_FLOAT_OOB_FILL_NONE);
    }
    conv_kernel<<<NUM_CTAS, 384, SMEM_BYTES>>>(xm, omap, (const char*)d_in[1], (const char*)d_in[0]);
}
```

```cpp
#include <cuda_runtime.h>
#include <cuda_bf16.h>
#include <cuda.h>
#include <stdint.h>

namespace {

#define GAPB 2
#define PKH0 3
#define PKH1 PKH0
#define PKH (RANK == 0 ? PKH0 : PKH1)
#define KPS0 2
#define KPS1 KPS0
#define KPS (RANK == 0 ? KPS0 : KPS1)
#define EPK0 11
#define EPK1 EPK0
#define EPK (RANK == 0 ? EPK0 : EPK1)
#define SPK0 15
#define SPK1 SPK0
#define SPK (RANK == 0 ? SPK0 : SPK1)
#define KPE 0
#define HKS 3
#define ST_EF
#define PF 6
#define PF0 5
#define EQ0 0x7fa
#define EQ1 0x7fe
#define PLA0 0xf0223445566ff045ull
#define PLA1 0xff012445566ff045ull
#define PLB0 0x4444459aab000000ull
#define PLB1 0x4444459aab000000ull
#define FMODE0 1
#define FMODE1 1
#define ORD 0
#define FMODE (RANK == 0 ? FMODE0 : FMODE1)
#define LT0 0
#define LT1 0
#define LATE(n) (((RANK == 0 ? LT0 : LT1) >> (n)) & 1)
#define LL0 0x10
#define LL1 0x10
#define LLATE(n) (((RANK == 0 ? LL0 : LL1) >> (n)) & 1)
#define PO0 0x012654
#define PO1 PO0
#define PG(g) (((RANK == 0 ? PO0 : PO1) >> (20 - (g) * 4)) & 7)
#define M1FIRST (PG(2) >= 4 ? PG(2) & 3 : PG(3) & 3)
#define EBSLOT (PG(2) == 2 ? 8 : PG(3) == 2 ? 9 : 10)
#define NW0 0
#define NW1 NW0
#define NW(n) (((RANK == 0 ? NW0 : NW1) >> (n)) & 1)
#define DEC 1
#define RORD 0x675231
#define PW0 0
#define PW1 1
#define EPO 0x8c04ab9231ull
#define PROMO CU_TENSOR_MAP_L2_PROMOTION_L2_128B
#define ZEND 1
#define HPIN 0
#define LL2 0x20
#define LLATE2(n) ((LL2 >> (n)) & 1)
#define CPT 0x01234
#define CP(k) ((CPT >> (16 - 4 * (k))) & 7)
#define MEF 0
#define DEFW 0
#define PKSLOT 7
#define EQ(n) (((RANK == 0 ? EQ0 : EQ1) >> (n)) & 1)
#define LAG0 6
#define LEAD0 9
#define LAG1 LAG0
#define LEAD1 LEAD0
#define LAGPOS (RANK == 0 ? LAG0 : LAG1)
#define LEADPOS (RANK == 0 ? LEAD0 : LEAD1)
#define LAGK (LEADPOS > 20 ? 1 : LEADPOS >= 12 || LEADPOS < LAGPOS ? 2 : 1)
#define SEND1 4
#define SEND2 6
#define TL(slot)
#define TLC(slot)
constexpr int IMG_H = 512, IMG_W = 512, CH = 96;
constexpr int IN_SLAB = 72 * 32;
constexpr int IN_ROW = 3 * IN_SLAB;
constexpr int SL0 = 0, SL4 = IN_SLAB, SL2 = 2 * IN_SLAB, SL3 = 3 * IN_SLAB, IN_B = 8 * IN_SLAB;
constexpr int W_K8 = 3 * 512;
constexpr int W_TAP = 6 * W_K8;
constexpr int W_COMP = 3 * W_TAP;
constexpr int W_BYTES = 5 * W_COMP;
constexpr int X_CH = 32 * 64;
constexpr int X_UNIT = 3 * X_CH;
constexpr int X_BYTES = 3 * X_UNIT;
constexpr int X_TX = X_UNIT;
constexpr int SEG = 32;
constexpr int NIT = 11;
constexpr int NUM_CTAS = 128;
#define LAY 3
constexpr int OFF_W = LAY == 0 ? 0 : LAY == 1 ? 2 * X_BYTES : LAY == 2 ? 2 * X_BYTES + 8 * IN_ROW : 8 * IN_ROW;
constexpr int OFF_X = LAY == 0 ? W_BYTES : LAY == 3 ? W_BYTES + 8 * IN_ROW : 0;
constexpr int OFF_IN = LAY == 3 ? 0 : LAY == 2 ? 2 * X_BYTES : W_BYTES + 2 * X_BYTES;
constexpr int OFF_BAR = W_BYTES + 2 * X_BYTES + 8 * IN_ROW;
constexpr int SMEM_BYTES = 1024 + OFF_BAR + 1024;
static_assert(SMEM_BYTES <= 232448, "smem");
#define RDEL 700
constexpr uint32_t ROW_DELAY = RDEL;
constexpr int B_FULL0 = 0, B_FULLA = 8, B_FULLB = 16, B_FULLC = 24, B_EMPTYE = 32, B_EMPTYF = 40, B_EMPTYB = 48, B_HFULL = 56,
              B_FFULL = 64, B_SH = 72, B_SF = 80;

__device__ __forceinline__ uint32_t smem_u32(const void* p) {
    return (uint32_t)__cvta_generic_to_shared(p);
}
__device__ __forceinline__ void mbar_init(uint32_t bar, uint32_t count) {
    asm volatile("mbarrier.init.shared::cta.b64 [%0], %1;" ::"r"(bar), "r"(count) : "memory");
}
__device__ __forceinline__ void mbar_expect_tx(uint32_t bar, uint32_t bytes) {
    asm volatile("mbarrier.arrive.expect_tx.shared::cta.b64 _, [%0], %1;" ::"r"(bar), "r"(bytes) : "memory");
}
__device__ __forceinline__ void mbar_arrive(uint32_t bar) {
    asm volatile("mbarrier.arrive.shared::cta.b64 _, [%0];" ::"r"(bar) : "memory");
}
__device__ __forceinline__ void mbar_arrive_warp(uint32_t bar) {
    __syncwarp();
    asm volatile("{\n\t.reg .pred p;\n\telect.sync _|p, 0xffffffff;\n\t@p mbarrier.arrive.shared::cta.b64 _, [%0];\n\t}" ::"r"(bar) : "memory");
}
__device__ __forceinline__ void mbar_arrive_remote(uint32_t rbar) {
    asm volatile("mbarrier.arrive.relaxed.cluster.shared::cluster.b64 _, [%0];" ::"r"(rbar) : "memory");
}
__device__ __forceinline__ void mbar_expect_tx_remote(uint32_t rbar, uint32_t bytes) {
    asm volatile("mbarrier.arrive.expect_tx.relaxed.cluster.shared::cluster.b64 _, [%0], %1;" ::"r"(rbar), "r"(bytes) : "memory");
}
__device__ __forceinline__ void mbar_wait(uint32_t bar, uint32_t parity) {
    uint32_t done;
    for (;;) {
        asm volatile(
            "{\n\t.reg .pred p;\n\t"
            "mbarrier.try_wait.parity.shared::cta.b64 p, [%1], %2;\n\t"
            "selp.u32 %0, 1, 0, p;\n\t}"
            : "=r"(done) : "r"(bar), "r"(parity) : "memory");
        if (done) return;
    }
}
#define STAMP(t, j)
__device__ __forceinline__ uint32_t mbar_try(uint32_t bar, uint32_t parity) {
    uint32_t done;
    asm volatile("{\n\t.reg .pred p;\n\tmbarrier.try_wait.parity.shared::cta.b64 p, [%1], %2;\n\tselp.u32 %0, 1, 0, p;\n\t}"
                 : "=r"(done) : "r"(bar), "r"(parity) : "memory");
    return done;
}
#define HSL 0
__device__ __forceinline__ void mbar_wait_h(uint32_t bar, uint32_t parity) {
    mbar_wait(bar, parity);
}
__device__ __forceinline__ bool elect() {
    uint32_t el;
    asm volatile("{\n\t.reg .pred p;\n\telect.sync _|p, 0xffffffff;\n\tselp.u32 %0, 1, 0, p;\n\t}" : "=r"(el));
    return el;
}
__device__ __forceinline__ uint32_t mapa(uint32_t addr, uint32_t rank) {
    uint32_t r;
    asm("mapa.shared::cluster.u32 %0, %1, %2;" : "=r"(r) : "r"(addr), "r"(rank));
    return r;
}
__device__ __forceinline__ void tma_load_5d(uint32_t dst, const CUtensorMap* map, uint32_t bar,
                                            int c0, int c1, int c2, int c3, int c4, bool keep) {
    asm volatile(
        "cp.async.bulk.tensor.5d.shared::cluster.global.mbarrier::complete_tx::bytes "
        "[%0], [%1, {%3, %4, %5, %6, %7}], [%2];"
        ::"r"(dst), "l"((uint64_t)map), "r"(bar), "r"(c0), "r"(c1), "r"(c2), "r"(c3), "r"(c4) : "memory");
}
#define EFN 99
#define EFM 7
#define EFM2 0
#define EF(t, u) ((((t) < EFN ? EFM : EFM2) >> (u)) & 1)
__device__ __forceinline__ void tma_store_4d(const CUtensorMap* map, uint32_t src, int c0, int c1, int c2, int c3, bool ef) {
    uint64_t pol, pn;
    asm volatile("createpolicy.fractional.L2::evict_first.b64 %0, 1.0;" : "=l"(pol));
    asm volatile("createpolicy.fractional.L2::evict_normal.b64 %0, 1.0;" : "=l"(pn));
    if (!ef) pol = pn;
    asm volatile("cp.async.bulk.tensor.5d.global.shared::cta.bulk_group.L2::cache_hint [%0, {%2, %2, %3, %2, %4}], [%1], %5;"
                 ::"l"((uint64_t)map), "r"(src), "r"(c0), "r"(c3 * 128 + c1), "r"(c2), "l"(pol) : "memory");
}
__device__ __forceinline__ void load_row(uint32_t dst, uint32_t dstb, const CUtensorMap* xmap, uint32_t fb, int rank, int strip, int row, bool keep) {
    tma_load_5d(dst, xmap + 1, fb, rank * 64, 0, strip * 16 - 1, 0, row, keep);
    tma_load_5d(dstb, xmap, fb, 32 + rank * 16, 0, strip * 16 - 1, 0, row, keep);
}

__device__ __forceinline__ void wgmma_fence() { asm volatile("wgmma.fence.sync.aligned;" ::: "memory"); }
__device__ __forceinline__ void wgmma_commit() { asm volatile("wgmma.commit_group.sync.aligned;" ::: "memory"); }
template <int N>
__device__ __forceinline__ void wgmma_wait() { asm volatile("wgmma.wait_group.sync.aligned %0;" ::"n"(N) : "memory"); }

template <int SA>
__device__ __forceinline__ void wgmma_m64n96k16(float (&d)[48], const uint32_t* a, uint64_t db, int scale_d) {
    asm volatile(
        "{\n\t.reg .pred p;\n\t"
        "setp.ne.b32 p, %53, 0;\n\t"
        "wgmma.mma_async.sync.aligned.m64n96k16.f32.bf16.bf16 "
        "{%0, %1, %2, %3, %4, %5, %6, %7, %8, %9, %10, %11, %12, %13, %14, %15, "
        " %16, %17, %18, %19, %20, %21, %22, %23, %24, %25, %26, %27, %28, %29, %30, %31, "
        " %32, %33, %34, %35, %36, %37, %38, %39, %40, %41, %42, %43, %44, %45, %46, %47}, "
        "{%48, %49, %50, %51}, %52, p, %54, 1, 1;\n\t}"
        : "+f"(d[0]), "+f"(d[1]), "+f"(d[2]), "+f"(d[3]), "+f"(d[4]), "+f"(d[5]), "+f"(d[6]), "+f"(d[7]),
          "+f"(d[8]), "+f"(d[9]), "+f"(d[10]), "+f"(d[11]), "+f"(d[12]), "+f"(d[13]), "+f"(d[14]), "+f"(d[15]),
          "+f"(d[16]), "+f"(d[17]), "+f"(d[18]), "+f"(d[19]), "+f"(d[20]), "+f"(d[21]), "+f"(d[22]), "+f"(d[23]),
          "+f"(d[24]), "+f"(d[25]), "+f"(d[26]), "+f"(d[27]), "+f"(d[28]), "+f"(d[29]), "+f"(d[30]), "+f"(d[31]),
          "+f"(d[32]), "+f"(d[33]), "+f"(d[34]), "+f"(d[35]), "+f"(d[36]), "+f"(d[37]), "+f"(d[38]), "+f"(d[39]),
          "+f"(d[40]), "+f"(d[41]), "+f"(d[42]), "+f"(d[43]), "+f"(d[44]), "+f"(d[45]), "+f"(d[46]), "+f"(d[47])
        : "r"(a[0]), "r"(a[1]), "r"(a[2]), "r"(a[3]), "l"(db), "r"(scale_d), "n"(SA));
}

template <int N>
__device__ __forceinline__ void fence_regs(float (&r)[N]) {
#pragma unroll
    for (int i = 0; i < N; ++i) asm volatile("" : "+f"(r[i])::"memory");
}

__device__ __forceinline__ uint32_t bf2_add(uint32_t a, uint32_t b) {
    uint32_t r;
    asm volatile("add.rn.bf16x2 %0, %1, %2;" : "=r"(r) : "r"(a), "r"(b));
    return r;
}
__device__ __forceinline__ uint32_t bf2_sub(uint32_t a, uint32_t b) {
    uint32_t r;
    asm volatile("sub.rn.bf16x2 %0, %1, %2;" : "=r"(r) : "r"(a), "r"(b));
    return r;
}
template <uint32_t B>
__device__ __forceinline__ uint32_t bf2_fma(uint32_t a, uint32_t cc) {
    uint32_t r;
    asm volatile("fma.rn.bf16x2 %0, %1, %2, %3;" : "=r"(r) : "r"(a), "r"(B), "r"(cc));
    return r;
}
__device__ __forceinline__ uint32_t pack_bf16(float a, float b) {
    __nv_bfloat162 v = __floats2bfloat162_rn(a, b);
    return *reinterpret_cast<uint32_t*>(&v);
}

__device__ __forceinline__ uint32_t opaque_add(uint32_t a, uint32_t b) {
    uint32_t r;
    asm volatile("add.u32 %0, %1, %2;" : "=r"(r) : "r"(a), "r"(b));
    return r;
}
template <int K>
__device__ __forceinline__ void make_quads(uint32_t (&q)[12], const uint32_t (&x)[24], const uint32_t (&d2)[24],
                                           const uint32_t (&u)[24], int kc, uint32_t coef = 0) {
    uint32_t e[8];
#pragma unroll
    for (int i = 0; i < 8; ++i) e[i] = K == 1 ? bf2_add(x[kc * 8 + i], d2[kc * 8 + i]) : bf2_sub(x[kc * 8 + i], d2[kc * 8 + i]);
#pragma unroll
    for (int jj = 0; jj < 3; ++jj) {
        const int j = jj == 0 ? 1 : jj == 1 ? 0 : 2;
#pragma unroll
        for (int hl = 0; hl < 2; ++hl) {
#pragma unroll
            for (int h = 0; h < 2; ++h) {
                const int i = ((j + h) >> 1) * 4 + hl * 2 + ((j + h) & 1);
                const uint32_t uu = u[kc * 8 + i];
                if (K < 0) asm volatile("fma.rn.bf16x2 %0, %1, %2, %3;" : "=r"(q[j * 4 + hl * 2 + h]) : "r"(uu), "r"(coef), "r"(e[i]));
                else q[j * 4 + hl * 2 + h] = K == 0 ? bf2_fma<0x3f003f00u>(uu, e[i]) : K == 1 ? bf2_sub(e[i], uu)
                                      : K == 2 ? bf2_fma<0x40404040u>(e[i], uu) : bf2_fma<0xc000c000u>(uu, e[i]);
            }
        }
    }
}
template <bool MAKE_U, bool TIE>
__device__ __forceinline__ void make_mid(uint32_t (&q)[12], uint32_t (&d1)[24], const uint32_t (&d2)[24], uint32_t (&u)[24], int kc,
                                         const uint32_t (&d3)[24], uint32_t wg) {
    uint32_t y[8];
#pragma unroll
    for (int i = 0; i < 8; ++i) {
        y[i] = bf2_sub(d2[kc * 8 + i], d3[kc * 8 + i]);
        if (MAKE_U) asm volatile("sub.rn.bf16x2 %0, %0, %1;" : "+r"(u[kc * 8 + i]) : "r"(d1[kc * 8 + i]));
        if (TIE) asm volatile("{\n\t.reg .pred q;\n\tsetp.ne.u32 q, %3, 7;\n\t@q fma.rn.bf16x2 %0, %0, %2, %1;\n\t}" : "+r"(d1[kc * 8 + i]) : "r"(y[i]), "r"(0x40004000u), "r"(wg));
        else asm volatile("fma.rn.bf16x2 %0, %0, %2, %1;" : "+r"(d1[kc * 8 + i]) : "r"(y[i]), "r"(0x40004000u));
    }
#pragma unroll
    for (int jj = 0; jj < 3; ++jj) {
        const int j = jj == 0 ? 1 : jj == 1 ? 0 : 2;
#pragma unroll
        for (int hl = 0; hl < 2; ++hl) {
#pragma unroll
            for (int h = 0; h < 2; ++h) {
                const int i = ((j + h) >> 1) * 4 + hl * 2 + ((j + h) & 1);
                q[j * 4 + hl * 2 + h] = bf2_fma<0x3fc03fc0u>(y[i], u[kc * 8 + i]);
            }
        }
    }
}

struct Ctx {
    uint32_t bar;
    uint32_t wdesc;
    uint32_t wready, wg, tlo, k, zero, tlo2, vz, ua;
    int rk;
    uint32_t ld0, ld1;
    uint32_t xbuf;
    uint32_t r_off;
};

__device__ __forceinline__ void sb(const Ctx& c) {
    asm volatile("{\n\t.reg .pred q;\n\tsetp.eq.u32 q, %1, 7;\n\t@q mov.u32 %0, %clock;\n\t}" : "+r"(const_cast<Ctx&>(c).vz) : "r"(c.wg) : "memory");
}
__device__ __forceinline__ void sbz(const Ctx& c) {
    asm volatile("{\n\t.reg .pred q;\n\tsetp.eq.u32 q, %1, 7;\n\t@q mov.u32 %0, %clock;\n\t}" : "+r"(const_cast<Ctx&>(c).zero) : "r"(c.wg) : "memory");
}
#define FTW(n)
#define FTM
__device__ __forceinline__ void sbk(Ctx& c) {
    asm volatile("{\n\t.reg .pred q;\n\tsetp.eq.u32 q, %1, 7;\n\t@q mov.u32 %0, %clock;\n\t}" : "+r"(c.k) : "r"(c.wg) : "memory");
}
template <int OFF>
__device__ __forceinline__ void ldsm(uint32_t* r, uint32_t a, uint32_t ua) {
    asm volatile("{\n\t.reg .u32 t;\n\tadd.u32 t, %4, %5;\n\tldmatrix.sync.aligned.m8n8.x4.shared.b16 {%0, %1, %2, %3}, [t + %6];\n\t}"
                 : "=r"(r[0]), "=r"(r[1]), "=r"(r[2]), "=r"(r[3]) : "r"(a), "r"(ua), "n"(OFF) : "memory");
}
template <bool PLUS>
__device__ __forceinline__ uint32_t addr2(uint32_t b, uint32_t t) {
    uint32_t r;
    if (PLUS) asm volatile("mad.lo.s32 %0, %1, 2, %2;" : "=r"(r) : "r"(b), "r"(t));
    else asm volatile("{\n\t.reg .s32 x;\n\tneg.s32 x, %2;\n\tmad.lo.s32 %0, %1, 2, x;\n\t}" : "=r"(r) : "r"(b), "r"(t));
    return r;
}
template <int SLOT, int KC>
__device__ __forceinline__ void ld_chunk_t(uint32_t (&r)[24], const Ctx& c, uint32_t ua, uint32_t ub) {
    if (KC == 2) {
        ldsm<SLOT>(&r[16], c.ld0, ub);
        ldsm<SLOT>(&r[20], c.ld1, ub);
    } else {
        ldsm<2 * SLOT + KC * 16>(&r[KC * 8], addr2<KC == 0>(c.ld0, c.vz), ua);
        ldsm<2 * SLOT + 16 - KC * 16>(&r[KC * 8 + 4], addr2<KC != 0>(c.ld1, c.vz), ua);
    }
}
#define ld_chunk(r, c, slot, kc) ld_chunk_t<slot, kc>(r, c, c.ua, 0)

__device__ __forceinline__ void mma3p(float (&acc)[48], const uint32_t* q0, const uint32_t* q1, const uint32_t* q2,
                                      const Ctx& c, int k, int kc, bool fresh) {
    uint32_t wd;
    asm volatile("mov.b32 %0, %1;" : "=r"(wd) : "r"(c.wdesc));
    wgmma_fence();
#pragma unroll
    for (int j = 0; j < 3; ++j) {
        const uint32_t lo = wd + (uint32_t)((CP(k) * W_COMP + j * W_TAP + (kc == 2 ? 4 - 4 * c.rk : kc + 2 * c.rk) * W_K8) >> 4);
        const uint32_t hi = (uint32_t)((kc == 2 ? W_K8 : 2 * W_K8) >> 4) | (2u << 30);
        uint64_t db;
        asm("mov.b64 %0, {%1, %2};" : "=l"(db) : "r"(lo), "r"(hi));
        if (k == 3 && c.rk == 1) wgmma_m64n96k16<-1>(acc, j == 0 ? q0 : j == 1 ? q1 : q2, db, (fresh && j == 0) ? 0 : 1);
        else wgmma_m64n96k16<1>(acc, j == 0 ? q0 : j == 1 ? q1 : q2, db, (fresh && j == 0) ? 0 : 1);
    }
    wgmma_commit();
}
__device__ __forceinline__ void mma3(float (&acc)[48], const uint32_t (&q)[12], const Ctx& c, int k, int kc, bool fresh) {
    mma3p(acc, &q[0], &q[4], &q[8], c, k, kc, fresh);
}
__device__ __forceinline__ void make_dup(uint32_t (&q)[12], const uint32_t (&u)[24], const Ctx& c, int kc) {
#pragma unroll
    for (int i = 0; i < 4; ++i)
        q[kc * 4 + i] = opaque_add(u[kc * 8 + (i & 1) * 3 + (i >> 1) * 2 + 1], c.zero);
}
__device__ __forceinline__ void mma3d(float (&acc)[48], const uint32_t (&u)[24], const uint32_t (&q)[12], const Ctx& c, int k, int kc, int first = 0) {
    mma3p(acc, &u[kc * 8], &q[kc * 4], &u[kc * 8 + 4], c, k, kc, kc == first);
}
__device__ __forceinline__ void mma3u(float (&acc)[48], const uint32_t (&u)[24], uint32_t (&q)[12], const Ctx& c, int kc) {
    make_dup(q, u, c, kc);
    mma3d(acc, u, q, c, 3, kc);
}

__device__ __forceinline__ uint32_t pack_word(const float (&acc)[48], int i, int m) {
    const int o = ((i % 3) * 4 + m) * 4 + (i / 3) * 2;
    return pack_bf16(acc[o], acc[o + 1]);
}
__device__ __forceinline__ void st_async(uint32_t addr, uint32_t r0, uint32_t r1, uint32_t r2, uint32_t r3, uint32_t rbar) {
    asm volatile("st.async.weak.shared::cluster.mbarrier::complete_tx::bytes.v4.b32 [%0], {%1, %2, %3, %4}, [%5];"
                 ::"r"(addr), "r"(r0), "r"(r1), "r"(r2), "r"(r3), "r"(rbar) : "memory");
}
template <int I>
__device__ __forceinline__ void send_acc(float (&acc)[48], uint32_t (&kp)[24], const Ctx& c, int n, int at, int spk) {
    if (n == (at < spk ? at : spk)) {
        fence_regs(acc);
#pragma unroll
        for (int m = 0; m < 4; ++m) {
            if (at > spk) asm volatile("add.rn.bf16x2 %0, %0, %1;" : "+r"(kp[I * 4 + m]) : "r"(pack_word(acc, I, m)));
            else kp[I * 4 + m] = GAPB == 2 ? bf2_add(pack_word(acc, I, m), kp[I * 4 + m]) : pack_word(acc, I, m);
        }
    }
    if (n != at) return;
    const uint32_t ro = c.r_off + (c.zero >> n), rx = c.xbuf + ro, rb = c.bar + B_FFULL + ro;
    st_async(rx + (I / 3) * X_UNIT + (I % 3) * X_CH, kp[I * 4], kp[I * 4 + 1], kp[I * 4 + 2], kp[I * 4 + 3], rb);
}
template <int I, bool H = true>
__device__ __forceinline__ void send_half(const uint32_t (&p)[12], const Ctx& c, int n = 0) {
    const uint32_t ro = c.r_off + (c.zero >> n), rx = c.xbuf + ro, rb = c.bar + (H ? B_HFULL : B_FFULL) + ro;
    st_async(rx + (H ? 2 * X_UNIT : 0) + I * X_CH, p[I * 4], p[I * 4 + 1], p[I * 4 + 2], p[I * 4 + 3], rb);
}
template <int I0, int N>
__device__ __forceinline__ void fin_pack(float (&acc)[48], uint32_t (&pk)[N * 4]) {
    fence_regs(acc);
#pragma unroll
    for (int i = 0; i < N * 4; ++i) {
        pk[i] = pack_word(acc, I0 + (i >> 2), i & 3);
        asm volatile("" : "+r"(pk[i]));
    }
}
template <int N>
__device__ __forceinline__ void fin_load(uint32_t (&v)[N * 4], const Ctx& c, int off) {
#pragma unroll
    for (int i = 0; i < N; ++i)
        asm volatile("ld.shared.v4.b32 {%0, %1, %2, %3}, [%4];"
                     : "=r"(v[i * 4 + 0]), "=r"(v[i * 4 + 1]), "=r"(v[i * 4 + 2]), "=r"(v[i * 4 + 3])
                     : "r"(c.xbuf + off + (i / 3) * X_UNIT + (i % 3) * X_CH) : "memory");
}
template <int N>
__device__ __forceinline__ void fin_store(uint32_t (&pk)[N * 4], const uint32_t (&v)[N * 4], const Ctx& c, int off, int sbar) {
#pragma unroll
    for (int i = 0; i < N; ++i) {
#pragma unroll
        for (int j = i * 4; j < i * 4 + 4; ++j) asm volatile("add.rn.bf16x2 %0, %0, %1;" : "+r"(pk[j]) : "r"(v[j]));
        asm volatile("st.shared.v4.b32 [%0], {%1, %2, %3, %4};"
                     ::"r"(c.xbuf + off + (i / 3) * X_UNIT + (i % 3) * X_CH), "r"(pk[i * 4]), "r"(pk[i * 4 + 1]), "r"(pk[i * 4 + 2]),
                       "r"(pk[i * 4 + 3]) : "memory");
    }
    if (sbar >= 0) mbar_arrive_warp(c.bar + sbar);
}

__device__ __forceinline__ void pin(const uint32_t* r, const Ctx& c) {
    asm volatile("{\n\t.reg .pred q;\n\tsetp.ne.u32 q, %12, 7;\n\t@q bra.uni PIN_SKIP;\n\t"
                 "st.volatile.shared.v4.b32 [%13], {%0, %1, %2, %3};\n\tst.volatile.shared.v4.b32 [%13], {%4, %5, %6, %7};\n\t"
                 "st.volatile.shared.v4.b32 [%13], {%8, %9, %10, %11};\n\tPIN_SKIP:\n\t}"
                 ::"r"(r[0]), "r"(r[1]), "r"(r[2]), "r"(r[3]), "r"(r[4]), "r"(r[5]), "r"(r[6]), "r"(r[7]), "r"(r[8]), "r"(r[9]),
                   "r"(r[10]), "r"(r[11]), "r"(c.wg), "r"(c.bar) : "memory");
}
__device__ __forceinline__ void pin4(const uint32_t* r, const Ctx& c) {
    asm volatile("{\n\t.reg .pred q;\n\tsetp.eq.u32 q, %4, 7;\n\t@q st.volatile.shared.v4.b32 [%5], {%0, %1, %2, %3};\n\t}"
                 ::"r"(r[0]), "r"(r[1]), "r"(r[2]), "r"(r[3]), "r"(c.wg), "r"(c.bar) : "memory");
}
__device__ __forceinline__ void acc_add(float& d, float x, float k) {
    asm volatile("fma.rn.f32 %0, %1, %2, %0;" : "+f"(d) : "f"(x), "f"(k));
}
__device__ __forceinline__ void acc_scale_add(float& d, float k, float x) {
    asm volatile("fma.rn.f32 %0, %0, %2, %1;" : "+f"(d) : "f"(x), "f"(k));
}
template <int RANK, int I0 = 0, int I1 = 24>
__device__ __forceinline__ void mid_row(float (&b)[48], const float (&k)[48], uint32_t (&ps)[12], uint32_t (&pk)[12],
                                        float f = -2.f) {
#pragma unroll
    for (int i = I0; i < I1; ++i) {
        const int ch = i >> 2, o = ((ch % 3) * 4 + (i & 3)) * 4 + (ch / 3) * 2;
        acc_scale_add(b[o], f, k[o]);
        acc_scale_add(b[o + 1], f, k[o + 1]);
        uint32_t& dst = (i / 12 == RANK) ? pk[i % 12] : ps[i % 12];
        dst = pack_bf16(b[o], b[o + 1]);
        asm volatile("" : "+r"(dst));
    }
}
template <int RANK>
__device__ __forceinline__ void mid_row2(float (&b)[48], const float (&k)[48], uint32_t (&ps)[12], uint32_t (&pk)[12], uint32_t (&kp)[24]) {
#pragma unroll
    for (int j = 0; j < 24; ++j) {
        const int i = EPK & 16 ? (j >> 1) + 12 * (j & 1) : (j + 12 - 12 * RANK) % 24;
        const int ch = i >> 2, o = ((ch % 3) * 4 + (i & 3)) * 4 + (ch / 3) * 2;
        const bool keep = i / 12 == RANK;
        uint32_t& dst = keep ? pk[i % 12] : ps[i % 12];
        if (!((PKH >> (keep ? 0 : 1)) & 1)) {
            acc_scale_add(b[o], -2.f, k[o]);
            acc_scale_add(b[o + 1], -2.f, k[o + 1]);
        }
        if (!((PKH & EPK) >> (keep ? 0 : 1) & 1)) dst = pack_bf16(b[o], b[o + 1]);
        if (!keep && (PKH & 2)) {
            kp[i] = pack_bf16(k[o], k[o + 1]);
            asm volatile("" : "+r"(kp[i]));
            dst = bf2_fma<0xc000c000u>(dst, kp[i]);
        }
        asm volatile("" : "+r"(dst));
    }
}
template <int RANK>
__device__ __forceinline__ void pack_k(const float (&k)[48], uint32_t (&kp)[24]) {
#pragma unroll
    for (int i = 0; i < 24; ++i) {
        if (i / 12 != RANK && (PKH & 2)) continue;
        kp[i] = pack_word(k, i >> 2, i & 3);
        asm volatile("" : "+r"(kp[i]));
    }
}
template <int RANK>
__device__ __forceinline__ void fix_hk(uint32_t (&hk)[12], const uint32_t (&kp)[24]) {
    if (PKH & 1) {
#pragma unroll
        for (int i = 0; i < 12; ++i) asm volatile("fma.rn.bf16x2 %0, %0, %2, %1;" : "+r"(hk[i]) : "r"(kp[RANK * 12 + i]), "r"(0xc000c000u));
    }
}
template <int I0, int I1>
__device__ __forceinline__ void acc_add_n(float (&d)[48], const float (&x)[48], float k) {
#pragma unroll
    for (int i = I0; i < I1; ++i) acc_add(d[i], x[i], k);
}

template <int RANK, bool LAST, int I0, int I1>
__device__ __forceinline__ void acc_add_pk(float (&d)[48], const float (&x)[48], float k, uint32_t (&ps)[12], uint32_t (&pk)[12]) {
    if (LAST || !(EPK & 3)) { acc_add_n<I0, I1>(d, x, k); return; }
#pragma unroll
    for (int j = I0 / 2; j < I1 / 2; ++j) {
        const int i = EPK & 8 ? (j >> 1) + 12 * (j & 1) : (j + 12 * ((EPK >> 2 ^ RANK) & 1)) % 24;
        const int ch = i >> 2, o = ((ch % 3) * 4 + (i & 3)) * 4 + (ch / 3) * 2;
        const bool keep = i / 12 == RANK;
        uint32_t& dst = keep ? pk[i % 12] : ps[i % 12];
        acc_add(d[o], x[o], k);
        acc_add(d[o + 1], x[o + 1], k);
        if ((PKH & EPK) >> (keep ? 0 : 1) & 1) {
            dst = pack_bf16(d[o], d[o + 1]);
            asm volatile("" : "+r"(dst));
        }
    }
}

#define LOCK 1
__device__ __forceinline__ void stagger_lead(const Ctx& c, uint32_t id) {
    if (LOCK) {
        asm volatile("{\n\t.reg .pred p;\n\tsetp.eq.u32 p, %1, 0;\n\t@p bar.sync %0, 256;\n\t}" ::"r"(id), "r"(c.wg) : "memory");
        return;
    }
    asm volatile("{\n\t.reg .pred p;\n\tsetp.eq.u32 p, %1, 0;\n\t@p bar.arrive %0, 256;\n\t}" ::"r"(id), "r"(c.wg) : "memory");
}
__device__ __forceinline__ void stagger_lag(const Ctx& c, uint32_t id) {
    asm volatile("{\n\t.reg .pred p;\n\tsetp.ne.u32 p, %1, 0;\n\t@p bar.sync %0, 256;\n\t}" ::"r"(id), "r"(c.wg) : "memory");
}

#define DEFM 0
#define M1O 0x012
#define M1O0 M1O
#define MO(i) (((RANK == 0 ? M1O0 : M1O) >> (8 - 4 * (i))) & 3)
#define QHW 1
#define CPY 0
#define LDP 0
#define DUPL 0
#define PQ0 0
#define PQ1 0
#define TIE0 0
#define TIE1 0
#define WA 0
#define WB 0
#define PKF (AT(23) == PKSLOT)
#define PROBE 0
#define PAPOS 0
#define PPOS 1
#define CS1 16
#define FT_BASE 538
template <int RANK, bool LAST>
__device__ __forceinline__ void phase1b(Ctx& c, float (&accS)[48], float (&accK)[48], float (&accC)[48],
                                        uint32_t (&d0)[24], uint32_t (&d1)[24], const uint32_t (&d2)[24],
                                        const uint32_t (&u)[24], uint32_t (&qd)[12], uint32_t (&qh)[12],
                                        uint32_t (&hs)[12], uint32_t (&hk)[12]) {
    uint32_t pa_ = 0;
    if ((PROBE & 1) && PAPOS == 0) pa_ = mbar_try(c.bar + B_FULLA, LAST ? (NIT - 1) & 1 : c.k & 1);
    fence_regs(accS);
    fence_regs(accC);
#pragma unroll
    for (int i = 0; i < 48; ++i)
        asm volatile("fma.rn.f32 %0, %1, %2, %3;" : "=f"(accK[i]) : "f"(accS[i]), "f"(RANK == 0 ? 1.f / 3.f : -4.f / 3.f), "f"(accC[i]));
    constexpr float CF = RANK == 0 ? -1.f / 6.f : -1.f / 3.f;
    if (DUPL) make_dup(qd, d1, c, MO(0));
    mma3d(accK, d1, qd, c, 1, MO(0), -1);
    sb(c);
    if ((PROBE & 1) && PAPOS == 1) pa_ = mbar_try(c.bar + B_FULLA, LAST ? (NIT - 1) & 1 : c.k & 1);
    if (!LAST && LEADPOS == 12) stagger_lead(c, c.k + 1);
    make_dup(qd, d1, c, MO(1));
    mma3d(accK, d1, qd, c, 1, MO(1), -1);
    sb(c);
    if ((PROBE & 1) && PAPOS == 2) pa_ = mbar_try(c.bar + B_FULLA, LAST ? (NIT - 1) & 1 : c.k & 1);
    if (!LAST && LEADPOS == 13) stagger_lead(c, c.k + 1);
    acc_add_pk<RANK, LAST, 0, CS1>(accC, accS, CF, hs, hk);
    if (PROBE & 16) sb(c);
    if (__builtin_expect(!pa_, PROBE & 1 ? 0 : 1)) mbar_wait(c.bar + B_FULLA, LAST ? (NIT - 1) & 1 : c.k & 1);
    if (WA == 1 && !LAST && c.k == 0) mbar_wait(c.bar + B_FULLA, 0);
    if (WA) sb(c);
    wgmma_wait<1>();
    if (LDP == 1) sb(c);
    if (LDP < 2) {
        if (RANK == 0 && !LAST) ld_chunk(d1, c, SL4, 0);
        else ld_chunk(d0, c, SL0, 0);
    }
    make_dup(qd, d1, c, MO(2));
    mma3d(accK, d1, qd, c, 1, MO(2), -1);
    sb(c);
    if (!LAST && LEADPOS == 14) stagger_lead(c, c.k + 1);
    if (LDP == 2) {
        if (RANK == 0 && !LAST) ld_chunk(d1, c, SL4, 0);
        else ld_chunk(d0, c, SL0, 0);
    }
    acc_add_pk<RANK, LAST, CS1, 48>(accC, accS, CF, hs, hk);
    sb(c);
    wgmma_wait<QHW>();
    if (LDP == 3) {
        if (RANK == 0 && !LAST) ld_chunk(d1, c, SL4, 0);
        else ld_chunk(d0, c, SL0, 0);
    }
    if (RANK == 0 && !LAST) make_quads<4>(qh, d1, d2, u, 0);
    else make_quads<0>(qh, d0, d2, u, 0);
    sb(c);
}

template <int RANK>
__device__ __forceinline__ void consumer(Ctx& c) {
    float accS[48], accK[48], accC[48];
    uint32_t d0[24], d1[24], d2[24], u[24];
    uint32_t qd[12];
#pragma unroll
    for (int i = 0; i < 48; ++i) { accS[i] = 0.f; accC[i] = 0.f; }
    {
        uint32_t qa[12], qe[12];
        mbar_wait(c.bar + B_FULL0, 0);
        c.rk = RANK;
        sbz(c);
        const uint32_t xo = (uint32_t)(OFF_X - OFF_IN) - c.wg * (4 * IN_ROW - X_BYTES);
        ld_chunk_t<0, 0>(d1, c, c.ua + xo, 0);
        ld_chunk(u, c, SL3, 0);
        ld_chunk_t<0, 1>(d1, c, c.ua + xo, 0);
        ld_chunk(u, c, SL3, 1);
        ld_chunk_t<0, 2>(d1, c, 0, xo + 2 * IN_SLAB - IN_B);
        ld_chunk(u, c, SL3, 2);
#pragma unroll
        for (int i = 0; i < 24; ++i) u[i] = bf2_sub(u[i], d1[i]);
#pragma unroll
        for (int kc = 0; kc < 3; ++kc) make_dup(qe, u, c, kc);
        TL(18);
        mbar_wait(c.wready, 0);
        TL(19);
#pragma unroll
        for (int kc = 0; kc < 3; ++kc) mma3d(accS, u, qe, c, 3, kc);
        mbar_wait(c.bar + B_FULLC, 0);
        ld_chunk(d2, c, SL2, 0);
        ld_chunk(d0, c, SL3, 0);
        ld_chunk(d2, c, SL2, 1);
        ld_chunk(d0, c, SL3, 1);
#pragma unroll
        for (int kc = 0; kc < 3; ++kc) {
            if (kc == 1) { sb(c); ld_chunk(d2, c, SL2, 2); ld_chunk(d0, c, SL3, 2); }
#pragma unroll
            for (int i = kc * 8; i < kc * 8 + 8; ++i) {
                asm volatile("sub.rn.bf16x2 %0, %1, %0;" : "+r"(d0[i]) : "r"(d2[i]));
                asm volatile("fma.rn.bf16x2 %0, %0, %2, %1;" : "+r"(d1[i]) : "r"(d0[i]), "r"(0x40004000u));
                asm volatile("fma.rn.bf16x2 %0, %0, %2, %1;" : "+r"(d0[i]) : "r"(u[i]), "r"(0x3fc03fc0u));
            }
            make_dup(qa, d0, c, kc);
            mma3d(accC, d0, qa, c, 2, kc);
        }
        mbar_arrive_warp(c.bar + B_EMPTYB);
        if (!DUPL) make_dup(qd, d1, c, MO(0));
        if (LAGK == 2) asm volatile("{\n\t.reg .pred p;\n\tsetp.ne.u32 p, %0, 0;\n\t@p bar.arrive 1, 256;\n\t}" ::"r"(c.wg) : "memory");
        if (WA == 2) mbar_wait(c.bar + B_FULLA, 0);
        wgmma_wait<0>();
        c.k = c.zero;
        TL(23);
    }
    constexpr int KA = RANK == 0 ? 4 : 0, KB = 4 - KA;
    constexpr int SA = RANK == 0 ? SL4 : SL0, SB = RANK == 0 ? SL0 : SL4;
    uint32_t (&ea)[24] = RANK == 0 ? d1 : d0;
    uint32_t (&eb)[24] = RANK == 0 ? d0 : d1;
#pragma unroll 1
    while (c.k < NIT - 1) {
#define par(n) ((c.k + (c.zero >> n)) & 1)
        uint32_t qa[12], qb[12], qe[12], qh[12], hs[12], hk[12];
        uint32_t hv[12], pa[12], pb[12], va[12], vb[12], kp[24], pb_ = 0, ph_ = 0, pf_ = 0;
        phase1b<RANK, false>(c, accS, accK, accC, d0, d1, d2, u, qd, qh, hs, hk);
#define AT(i) (int)(((RANK == 0 ? (i < 16 ? PLA0 : PLB0) : (i < 16 ? PLA1 : PLB1)) >> (60 - 4 * (i & 15))) & 15)
#define SLOT(n)                                                                                   \
        if (AT(2) == n && FMODE != 1) mbar_wait(c.bar + B_FULL0 + FMODE * 8, par(n));             \
        if (PPOS == 0) { PROBES(n) } if (AT(5) == n && __builtin_expect(!pb_, PROBE & 2 ? 0 : 1)) mbar_wait(c.bar + B_FULLB, par(n));                         \
        if (AT(14) == n && __builtin_expect(!ph_, PROBE & 4 ? 0 : 1)) mbar_wait(c.bar + B_HFULL, par(n));                                      \
        if (AT(22) == n && __builtin_expect(!pf_, PROBE & 8 ? 0 : 1)) mbar_wait(c.bar + B_FFULL, par(n));                                      \
        if (n == 2) mbar_arrive_warp(c.bar + B_EMPTYE);                                           \
        if (n == 5) mbar_arrive_warp(c.bar + B_EMPTYF);                                           \
        if (n == EBSLOT) mbar_arrive_warp(c.bar + B_EMPTYB);                                      \
        if (!LLATE(n)) { LOADS(n) }                                                               \
        if (!LATE(n)) { STORES(n) }                                                               \
        if (PPOS == 1) { PROBES(n) }
#define PROBES(n)                                                                                 \
        if ((PROBE & 2) && AT(5) == n + 1) pb_ = mbar_try(c.bar + B_FULLB, par(n));              \
        if ((PROBE & 4) && AT(14) == n + 1) ph_ = mbar_try(c.bar + B_HFULL, par(n));              \
        if ((PROBE & 8) && AT(22) == n + 1) pf_ = mbar_try(c.bar + B_FFULL, par(n));
#define LOADS(n)                                                                                  \
        if (AT(0) == n) ld_chunk(ea, c, SA, 1);                                                   \
        if (AT(1) == n) ld_chunk(ea, c, SA, 2);                                                   \
        if (AT(2) == n) ld_chunk(eb, c, SB, 0);                                                   \
        if (AT(3) == n) ld_chunk(eb, c, SB, 1);                                                   \
        if (AT(4) == n) ld_chunk(eb, c, SB, 2);                                                   \
        if (AT(5) == n) ld_chunk(u, c, SL3, 0);                                                   \
        if (AT(6) == n) ld_chunk(d2, c, SL2, 0);                                                  \
        if (AT(7) == n) ld_chunk(u, c, SL3, 1);                                                   \
        if (AT(8) == n) ld_chunk(d2, c, SL2, 1);                                                  \
        if (AT(9) == n) ld_chunk(u, c, SL3, 2);                                                   \
        if (AT(10) == n) ld_chunk(d2, c, SL2, 2);                                                 \
        if (AT(14) == n) fin_load<3>(hv, c, 2 * X_UNIT);                                          \
        if (AT(22) == n) fin_load<3>(va, c, 0);                                                   \
        if (AT(24) == n) fin_load<3>(vb, c, X_UNIT);
#define STORES(n)                                                                                 \
        if (n == PKSLOT && PKF) { fin_pack<0, 3>(accK, pa); fin_pack<3, 3>(accK, pb); if (AT(23) != n) pin(pa, c); if (AT(25) != n) pin(pb, c); } \
        if (AT(15) == n) fin_store<3>(hk, hv, c, 2 * X_UNIT, B_SH);                               \
        if (AT(23) == n) fin_store<3>(pa, va, c, 0, -1);                                          \
        if (AT(25) == n) fin_store<3>(pb, vb, c, X_UNIT, B_SF);                                   \
        if (LLATE(n) && !LLATE2(n)) { LOADS(n) }                                                  \
        if (AT(11) == n) send_half<0>(hs, c, n);                                                  \
        if (AT(12) == n) send_half<1>(hs, c, n);                                                  \
        if (AT(13) == n) send_half<2>(hs, c, n);                                                  \
        send_acc<0>(accS, kp, c, n, AT(16), SPK);                                          \
        send_acc<3>(accS, kp, c, n, AT(17), SPK);                                          \
        send_acc<1>(accS, kp, c, n, AT(18), SPK);                                          \
        send_acc<4>(accS, kp, c, n, AT(19), SPK);                                          \
        send_acc<2>(accS, kp, c, n, AT(20), SPK);                                          \
        send_acc<5>(accS, kp, c, n, AT(21), SPK);                                          \
        if (LLATE(n) && LLATE2(n)) { LOADS(n) }                                                   \
        if (n == PKSLOT && !PKF) { fin_pack<0, 3>(accK, pa); fin_pack<3, 3>(accK, pb); pin(pa, c); pin(pb, c); }
#define QW(n, Q)                                                                     \
        if (LATE(n)) { Q; sb(c); STORES(n); sb(c); wgmma_wait<1 + NW(n)>(); FTW(n); }        \
        else if (EQ(n)) { Q; sb(c); wgmma_wait<1 + NW(n)>(); FTW(n); } else { sb(c); wgmma_wait<1 + NW(n)>(); FTW(n); Q; } \
        if (PPOS == 2) { PROBES(n) }                                                              \
        if (LAGPOS == n) stagger_lag(c, c.k + LAGK);                                              \
        if (LEADPOS == n) stagger_lead(c, c.k + 1);
#define P1(g, q)                                                                                  \
        SLOT(g + 5);                                                                              \
        if (PG(g) < 4) {                                                                          \
            QW(g + 5, (make_mid<true, (((RANK == 0 ? TIE0 : TIE1) >> (PG(g) & 3)) & 1) != 0>(q, d1, d2, u, PG(g) & 3, u, c.wg)));                                 \
            mma3(accC, q, c, 2, PG(g) & 3, g == 0);                                               \
        } else {                                                                                  \
            QW(g + 5, make_dup(qe, u, c, PG(g) & 3));                                             \
            mma3d(accS, u, qe, c, 3, PG(g) & 3, M1FIRST);                                         \
        }
        if (!GAPB) {
            wgmma_wait<0>();
            fence_regs(accK);
            if (!DEFM) {
                mid_row<RANK>(accC, accK, hs, hk);
                pin(hk, c);
                SLOT(15);
            } else {
                LOADS(15);
            }
            sbk(c);
            acc_add_n<0, 48>(accS, accK, 1.f);
            mma3(accS, qh, c, KA, 0, false);
            sb(c);
            if (DEFM) {
                mid_row<RANK>(accC, accK, hs, hk);
                pin(hk, c);
                STORES(15);
                sb(c);
            }
        } else {
            mma3(accS, qh, c, KA, 0, false);
            wgmma_wait<1>();
            fence_regs(accK);
            LOADS(15);
            sbk(c);
            if (GAPB == 2) mid_row2<RANK>(accC, accK, hs, hk, kp);
            else mid_row<RANK>(accC, accK, hs, hk);
            pin(hk, c);
            STORES(15);
            sb(c);
        }
#define PK_(n, e) if (GAPB == 2 && KPS == n && KPE == e) pack_k<RANK>(accK, kp); if (GAPB == 2 && HKS == n && KPE == e) fix_hk<RANK>(hk, kp);
        PK_(0, 2)
        SLOT(0);
        PK_(0, 1)
        make_quads<KA>(qa, ea, d2, u, 1);
        PK_(0, 0)
        mma3(accS, qa, c, KA, 1, false);
        sb(c);
        PK_(1, 2)
        SLOT(1);
        PK_(1, 1)
        QW(1, make_quads<KA>(qb, ea, d2, u, 2); PK_(1, 0));
        mma3(accS, qb, c, KA, 2, false);
        sb(c);
        PK_(2, 2)
        SLOT(2);
        PK_(2, 1)
        QW(2, make_quads<KB>(qa, eb, d2, u, 0); PK_(2, 0));
        if (WB) mbar_wait(c.bar + B_FULLB, par(2));
        if (WB == 2) mbar_wait(c.bar + B_HFULL, par(2));
        if (GAPB == 1) {
            wgmma_wait<0>();
            fence_regs(accS);
            acc_add_n<0, 48>(accS, accK, 1.f);
        }
        mma3(accK, qa, c, KB, 0, false);
        sb(c);
        PK_(3, 2)
        SLOT(3);
        PK_(3, 1)
        QW(3, make_quads<KB>(qb, eb, d2, u, 1); PK_(3, 0));
        mma3(accK, qb, c, KB, 1, false);
        sb(c);
        PK_(4, 2)
        SLOT(4);
        QW(4, make_quads<KB>(qa, eb, d2, u, 2));
        mma3(accK, qa, c, KB, 2, false);
        sb(c);
        P1(0, qb);

        sb(c);
        P1(1, qa);

        sb(c);
        P1(2, qb);

        sb(c);
        P1(3, qa);

        sb(c);
        P1(4, qb);

        sb(c);
        P1(5, qa);

        sb(c);
        SLOT(11);
        if (LAGPOS == 11) stagger_lag(c, c.k + LAGK);
        if (LEADPOS == 11) stagger_lead(c, c.k + 1);
        if (!DUPL) make_dup(qd, d1, c, MO(0));
#pragma unroll
        for (int i = 0; i < 12; ++i)
            if (((RANK == 0 ? PQ0 : PQ1) >> i) & 1) pin4(&d2[(i % 6) * 4], c);
        sbz(c);
        ++c.k;
        if (WA) mbar_wait(c.bar + B_FULLA, c.k & 1);
        wgmma_wait<0>();
        TL(1 + c.k);
#undef par
    }
    {
        constexpr uint32_t par = (NIT - 1) & 1;
        uint32_t qa[12], qb[12], qh[12], hs[12], hk[12], v[12];
        constexpr int S0 = 12 - 12 * RANK, K0 = 12 * RANK;
        uint32_t pk[12];
        if (LAGK == 2) stagger_lead(c, NIT);
        phase1b<RANK, true>(c, accS, accK, accC, d0, d1, d2, u, qd, qh, hs, hk);
        mma3(accS, qh, c, 0, 0, RANK == 0);
        wgmma_wait<1>();
        ld_chunk(d0, c, SL0, 1);
        ld_chunk(d0, c, SL0, 2);
        fence_regs(accK);
        mid_row<RANK, S0, S0 + 12>(accC, accK, hs, hk);
        send_half<0>(hs, c);
        send_half<1>(hs, c);
        send_half<2>(hs, c);
        sb(c);
        make_quads<0>(qa, d0, d2, u, 1);
        mma3(accS, qa, c, 0, 1, false);
        make_quads<0>(qb, d0, d2, u, 2);
        mma3(accS, qb, c, 0, 2, false);
        mid_row<RANK, K0, K0 + 12>(accC, accK, hs, hk);
        mbar_wait(c.bar + B_FULLB, par);
        wgmma_wait<0>();
        fence_regs(accS);
        mid_row<RANK, S0, S0 + 12>(accS, accK, hs, pk, 1.f);
        send_half<0, false>(hs, c);
        send_half<1, false>(hs, c);
        send_half<2, false>(hs, c);
        mbar_wait(c.bar + B_HFULL, par);
        fin_load<3>(v, c, 2 * X_UNIT);
        mid_row<RANK, K0, K0 + 12>(accS, accK, hs, pk, 1.f);
        fin_store<3>(hk, v, c, 2 * X_UNIT, B_SH);
        mbar_wait(c.bar + B_FFULL + c.zero, par);
        fin_load<3>(v, c, 0);
        fin_store<3>(pk, v, c, 0, B_SF);
        TL(17);
    }
}

__device__ __forceinline__ void wt_load(uint32_t (&g)[36], uint32_t unit, int lane) {
    const uint32_t src = unit + (lane >> 2) * 192 + ((lane & 3) << 4);
#pragma unroll
    for (int i = 0; i < 9; ++i)
        asm volatile("ld.shared.v4.b32 {%0, %1, %2, %3}, [%4];"
                     : "=r"(g[i * 4]), "=r"(g[i * 4 + 1]), "=r"(g[i * 4 + 2]), "=r"(g[i * 4 + 3])
                     : "r"(src + (i / 3) * 64 + (i % 3) * 2 * W_COMP) : "memory");
}
__device__ __forceinline__ void stsm(uint32_t addr, const uint32_t* v) {
    asm volatile("stmatrix.sync.aligned.m8n8.x4.shared.b16 [%0], {%1, %2, %3, %4};"
                 ::"r"(addr), "r"(v[0]), "r"(v[1]), "r"(v[2]), "r"(v[3]) : "memory");
}
template <int PART>
__device__ __forceinline__ void wt_store(const uint32_t (&g)[36], uint32_t unit, int lane) {
    const uint32_t dst = unit + (lane & 7) * 64 + ((((lane >> 3) ^ (lane >> 1)) & 3) << 4);
    __syncwarp();
#pragma unroll
    for (int r = 0; r < 3; ++r) {
        const uint32_t *a = &g[r * 12], *b = a + 4, *cc = a + 8;
        uint32_t u1[4], u2[4], u3[4];
#pragma unroll
        for (int i = 0; i < 4; ++i) {
            uint32_t h;
            asm("add.rn.bf16x2 %0, %1, %2;" : "=r"(h) : "r"(a[i]), "r"(cc[i]));
            asm("mul.rn.bf16x2 %0, %1, %2;" : "=r"(h) : "r"(h), "r"(0x3f003f00u));
            asm("fma.rn.bf16x2 %0, %1, %2, %3;" : "=r"(u1[i]) : "r"(b[i]), "r"(0x3f003f00u), "r"(h));
            asm("fma.rn.bf16x2 %0, %1, %2, %3;" : "=r"(u2[i]) : "r"(b[i]), "r"(0xbf00bf00u), "r"(h));
            asm("mul.rn.bf16x2 %0, %1, %2;" : "=r"(h) : "r"(u2[i]), "r"(0xbaabbaabu));
            asm("fma.rn.bf16x2 %0, %0, %1, %2;" : "+r"(u2[i]) : "r"(0x3f2b3f2bu), "r"(h));
            asm("fma.rn.bf16x2 %0, %1, %2, %3;" : "=r"(h) : "r"(a[i]), "r"(0x3e803e80u), "r"(cc[i]));
            asm("fma.rn.bf16x2 %0, %1, %2, %3;" : "=r"(u3[i]) : "r"(h), "r"(0x40004000u), "r"(b[i]));
        }
        if (PART & 1) {
            stsm(dst + r * 512 + CP(2) * W_COMP, u2);
            stsm(dst + r * 512 + CP(1) * W_COMP, u1);
            stsm(dst + r * 512 + CP(3) * W_COMP, u3);
        }
        if (PART & 2) {
            stsm(dst + r * 512 + CP(0) * W_COMP, a);
            stsm(dst + r * 512 + CP(4) * W_COMP, cc);
        }
    }
}

__device__ __forceinline__ int seq_row(int seg, int row_par, int n) {
    const int q = (seg & 1) ? seg * SEG - 1 + n : seg * SEG + SEG - n;
    return 2 * q + row_par;
}

struct XMaps { CUtensorMap m[2]; };
#define xmap xm.m[0]
__global__ void __cluster_dims__(2, 1, 1) __launch_bounds__(384, 1)
conv_kernel(const __grid_constant__ XMaps xm, const __grid_constant__ CUtensorMap omap,
            const char* __restrict__ wp, const char* __restrict__ xp) {
    extern __shared__ uint8_t smem_raw[];
    const uint32_t base = (smem_u32(smem_raw) + 1023u) & ~1023u;
    const uint32_t wbase = base + OFF_W;
    const uint32_t bar_base = base + OFF_BAR;
    const uint32_t wbar_b = bar_base + 256, wready_b = bar_base + 280;

    const int tid = threadIdx.x;
    const int warp = tid >> 5, lane = tid & 31;
    const int rank = blockIdx.x & 1;
    const int cluster = blockIdx.x >> 1;
    const int strip = cluster & 7, seg = cluster >> 3;
    const int fmode = rank ? FMODE1 : FMODE0;
    uint32_t c_start;
    asm volatile("mov.u32 %0, %clock;" : "=r"(c_start) :: "memory");

    const int uwarp = __shfl_sync(0xffffffffu, warp, 0);
    const bool el = elect();
#define PFW 3
#define PFBLK                                                                                                \
    if (uwarp == PFW) {                                                                                      \
        if (lane < 20) {                                                                                     \
            const char* p = wp + (size_t)(((blockIdx.x & 63) * 20 + lane + (blockIdx.x >> 6) * 16) * 128);   \
            asm volatile("prefetch.global.L2 [%0];" ::"l"(p) : "memory");                                    \
        }                                                                                                    \
    }
#define PFPOS 0
    if (PFPOS == 0) { PFBLK }
    if (uwarp == 0 && el) {
        for (int i = 0; i < 3; ++i) mbar_init(wbar_b + i * 8, 1);
        asm volatile("fence.proxy.async.shared::cta;" ::: "memory");
        const int up = (seg & 1) ^ 1;
#pragma unroll
        for (int j = 0; j < 3; ++j) {
#pragma unroll
            for (int i = 0; i < 3; ++i)
                asm volatile("cp.async.bulk.shared::cluster.global.mbarrier::complete_tx::bytes [%0], [%1], %2, [%3];"
                             ::"r"(wbase + ((up ? 2 - i : i) * 6 + j) * W_TAP), "l"(wp + (2 * (i * 3 + j) + rank) * W_TAP),
                               "r"(W_TAP), "r"(wbar_b + j * 8) : "memory");
        }
        for (int j = 0; j < 3; ++j) mbar_expect_tx(wbar_b + j * 8, 3 * W_TAP);
        asm volatile("fence.mbarrier_init.release.cluster;" ::: "memory");
    }
    if (PFPOS == 1) { PFBLK }
#define RT 320
    if (uwarp == 2 && el) {
        for (int i = 0; i < 2; ++i) {
            mbar_init(bar_base + i * 128 + B_FULLA, 3);
            mbar_init(bar_base + i * 128 + B_FULLB, 2);
            mbar_init(bar_base + i * 128 + B_EMPTYE, 4);
            mbar_init(bar_base + i * 128 + B_EMPTYF, 4);
            mbar_init(bar_base + i * 128 + B_EMPTYB, 4);
            mbar_init(bar_base + i * 128 + B_HFULL, 1);
            mbar_init(bar_base + i * 128 + B_FFULL, 1);
            mbar_init(bar_base + i * 128 + B_SH, 4);
            mbar_init(bar_base + i * 128 + B_SF, 4);
            mbar_expect_tx(bar_base + i * 128 + B_HFULL, X_TX);
            mbar_expect_tx(bar_base + i * 128 + B_FFULL, 2 * X_TX);
            mbar_arrive(bar_base + i * 128 + B_FULLA);
        }
        mbar_init(wready_b, 10);
        asm volatile("fence.mbarrier_init.release.cluster;" ::: "memory");
        asm volatile("fence.proxy.async.shared::cta;" ::: "memory");
    }
    if (uwarp == 10 && el) {
        asm volatile("prefetch.tensormap [%0];" ::"l"((uint64_t)(&xmap)) : "memory");
        asm volatile("prefetch.tensormap [%0];" ::"l"((uint64_t)(&xmap + 1)) : "memory");
        for (int i = 0; i < 4; ++i) mbar_init(bar_base + (i >> 1) * 128 + (i & 1) * B_FULLC, 1);
        for (int i = 0; i < 4; ++i) mbar_expect_tx(bar_base + (i >> 1) * 128 + (i & 1) * B_FULLC, (2 - (i & 1)) * IN_ROW);
        asm volatile("fence.mbarrier_init.release.cluster;" ::: "memory");
        asm volatile("fence.proxy.async.shared::cta;" ::: "memory");
    }
    __syncwarp();
    asm volatile("barrier.cluster.arrive.relaxed.aligned;" ::: "memory");
#define RSTEP 150
    if (uwarp == 10 && el) {
#pragma unroll
        for (int i = 0; i < 6; ++i) {
            const int wg = (RORD >> (i * 4 + 2)) & 1, n = (RORD >> (i * 4)) & 3;
            const uint32_t fb = bar_base + wg * 128 + (n == 2 ? B_FULLC : B_FULL0);
            if (i == 0 || RSTEP) while ((uint32_t)clock() - c_start < ROW_DELAY + i * RSTEP) {}
            const uint32_t dst = base + (n == 1 ? OFF_X + wg * X_BYTES : OFF_IN + wg * 4 * IN_ROW + n * 2 * IN_SLAB);
            load_row(dst, dst + (n == 1 ? 2 * IN_SLAB : IN_B - n * IN_SLAB), &xmap, fb, rank, strip, seq_row(seg, wg, n), true);
        }
    }
    __syncwarp();
#define ST(j)
    ST(0);
    asm volatile("barrier.cluster.wait.aligned;" ::: "memory");
#define WX 4
#define HW0 11
#define HW1 9
    if (uwarp < 8 || uwarp == HW0 || uwarp == HW1) {
        uint32_t ga[36], gb[36];
        const int uw = uwarp < 8 ? uwarp ^ WX : uwarp == HW0 ? 8 : 9;
        const uint32_t unit = wbase + uw * W_K8;
        ST(1);
        if (uw < 8) {
            mbar_wait(wbar_b + (uw < 6 ? 0 : 8), 0);
            ST(2);
            wt_load(ga, unit, lane);
        }
        mbar_wait(wbar_b + (uw < 4 ? 8 : 16), 0);
        ST(3);
        wt_load(gb, unit + 8 * W_K8, lane);
        if (uw < 8) wt_store<3>(ga, unit, lane);
        ST(4);
        wt_store<3>(gb, unit + 8 * W_K8, lane);
        ST(5);
        asm volatile("fence.proxy.async.shared::cta;" ::: "memory");
        mbar_arrive_warp(wready_b);
        ST(6);
    }

    if (uwarp >= 8) {
        asm volatile("setmaxnreg.dec.sync.aligned.u32 24;");
        {
            const int wg = uwarp & 1;
            const uint32_t bar = bar_base + wg * 128;
            const int step = (seg & 1) ? 2 : -2;
            if (uwarp < 10) {
                const uint32_t in = base + OFF_IN + wg * 4 * IN_ROW;
                const char* pf = xp + (strip * 64 + rank * 32) * 192;
                int row = seq_row(seg, wg, 0);
#pragma unroll 1
                for (int t = 0; t < NIT; ++t, row += 3 * step) {
#pragma unroll
                    for (int g = 0; g < 3; ++g) {
                        const int sl = g == 2 ? 2 : (g ^ rank ^ 1);
                        const uint32_t fb = bar + (g == 2 ? B_FULLB : B_FULLA);
                        mbar_wait_h(bar + B_EMPTYE + g * 8, t & 1);
                        STAMP(t, 6 + g);
                        if (el) {
                            const bool ld = t < NIT - 1 || sl == 0;
                            if (ld) {
                                if (g == 2) load_row(in + 2 * SL3, in + IN_B + SL3, &xmap, fb, rank, strip, row + 6 * step, true);
                                load_row(in + sl * 2 * IN_SLAB, in + IN_B + sl * IN_SLAB, &xmap, fb, rank, strip, row + (g == 2 ? 5 : 4 * sl) * step, true);
                            }
                            mbar_expect_tx(fb, ld ? (g == 2 ? 2 * IN_ROW : IN_ROW) : 0);
                            if (g == 2 && t == 0) mbar_arrive_remote(mapa(fb, rank ^ 1));
                            const int n = 3 * t + g + 1, prow = row + (g + 1 + PF) * step;
                            if (n >= PF0 && n + PF < SEG + 2 && (unsigned)prow < IMG_H)
                            {
                                asm volatile("cp.async.bulk.prefetch.L2.global [%0], %1;"
                                             ::"l"(pf + (size_t)prow * (IMG_W * 192)), "r"(32 * 192) : "memory");
                            }
                        }
                        __syncwarp();
                        if (g) STAMP(t, 8 + g);
                    }
                }
            } else {
                const uint32_t src = base + OFF_X + wg * X_BYTES;
                const uint32_t r_bar = mapa(bar, rank ^ 1);
                if (wg == 0 && lane < 4)
                    asm volatile("mbarrier.arrive.shared::cta.b64 _, [%0], 4;" ::"r"(bar + (lane >> 1) * 128 + B_EMPTYE + (lane & 1) * 8) : "memory");
                __syncwarp();
                int row = seq_row(seg, wg, 1);
#pragma unroll 1
                for (int t = 0; t < NIT; ++t, row += 3 * step) {
                    const bool last = t == NIT - 1;
                    mbar_wait_h(bar + B_SH, t & 1);
                    STAMP(t, 0);
                    if (el) {
                        asm volatile("fence.proxy.async.shared::cta;" ::: "memory");
                        tma_store_4d(&omap, src + 2 * X_UNIT, 0, strip * 16, rank, row + step, EF(t, 2));
                        asm volatile("cp.async.bulk.commit_group;" ::: "memory");
                        if (!last) {
                            mbar_expect_tx(bar + B_HFULL, X_TX);
                            asm volatile("cp.async.bulk.wait_group.read 0;" ::: "memory");
                            mbar_arrive_remote(r_bar + B_FULLA);
                        }
                    }
                    __syncwarp();
                    STAMP(t, 1);
                    mbar_wait_h(bar + B_SF, t & 1);
                    STAMP(t, 2);
                    if (el) {
                        asm volatile("fence.proxy.async.shared::cta;" ::: "memory");
                        const int orow = row + (last ? 0 : 2 * rank * step);
                        tma_store_4d(&omap, src, 0, strip * 16, last ? rank : 0, orow, EF(t, 0));
                        if (!last) tma_store_4d(&omap, src + X_UNIT, 0, strip * 16, 1, orow, EF(t, 1));
                        asm volatile("cp.async.bulk.commit_group;" ::: "memory");
                        if (!last) mbar_expect_tx(bar + B_FFULL, t == NIT - 2 ? X_TX : 2 * X_TX);
                        asm volatile("cp.async.bulk.wait_group.read 0;" ::: "memory");
                        if (!last) mbar_arrive_remote(r_bar + B_FULLB);
                    }
                    __syncwarp();
                    STAMP(t, 3);
                }
            }
        }
    } else {
        const int wg = uwarp >> 2;
        const int w4 = warp & 3;
        if (RT >= 256) asm volatile("setmaxnreg.inc.sync.aligned.u32 240;");
        ST(7);
        Ctx c;
        c.bar = bar_base + wg * 128;
        c.wdesc = ((wbase & 0x3FFFF) >> 4) | ((uint32_t)(512 >> 4) << 16);
        c.wready = wready_b;
        c.wg = wg;
        c.k = ~0u;
        c.zero = 0;
        c.tlo2 = bar_base + 576 - bar_base * 4;
        c.tlo = 320;
        {
            const int m = lane >> 3, gg = lane & 7, hl = m >> 1;
            const int rho0 = (m & 1) ? (8 * w4 + gg + 2) : (36 + 8 * w4 + gg);
            const int rho1 = rho0 + 2;
            const uint32_t in = base + OFF_IN + wg * 4 * IN_ROW;
            c.ld0 = in + IN_B + rho0 * 32 + ((hl ^ ((rho0 >> 2) & 1)) << 4);
            c.ld1 = in + IN_B + rho1 * 32 + ((hl ^ ((rho1 >> 2) & 1)) << 4);
            c.vz = (rho0 & 2) << 3;
            c.ua = in - 2 * (in + IN_B);
        }
        c.xbuf = base + OFF_X + wg * X_BYTES + (tid & 127) * 16;
        c.r_off = mapa(c.bar, rank ^ 1) - c.bar;
        c.ld0 = __shfl_sync(0xffffffffu, c.ld0, lane);
        c.ld1 = __shfl_sync(0xffffffffu, c.ld1, lane);
        c.xbuf = __shfl_sync(0xffffffffu, c.xbuf, lane);
        TL(1);
        TLC(20);
        if (rank == 0) consumer<0>(c);
        else consumer<1>(c);
        TLC(21);
    }
}

typedef CUresult (*EncodeFn)(CUtensorMap*, CUtensorMapDataType, cuuint32_t, void*, const cuuint64_t*,
                             const cuuint64_t*, const cuuint32_t*, const cuuint32_t*, CUtensorMapInterleave,
                             CUtensorMapSwizzle, CUtensorMapL2promotion, CUtensorMapFloatOOBfill);

}

extern "C" void kernel_launch(void* const* d_in, const int* in_sizes, int n_in, void* d_out, int out_size) {
    (void)in_sizes; (void)n_in; (void)out_size;
    static EncodeFn encode = nullptr;
    if (!encode) {
        void* fn = nullptr;
        cudaDriverEntryPointQueryResult qres;
        cudaGetDriverEntryPoint("cuTensorMapEncodeTiled", &fn, cudaEnableDefault, &qres);
        encode = (EncodeFn)fn;
        cudaFuncSetAttribute(conv_kernel, cudaFuncAttributeMaxDynamicSharedMemorySize, SMEM_BYTES);
    }
    XMaps xm;
    CUtensorMap omap;
    cuuint32_t estr5[5] = {1, 1, 1, 1, 1};
    {
        cuuint64_t dims[5] = {(cuuint64_t)CH, 2, (cuuint64_t)IMG_W / 4, 2, (cuuint64_t)IMG_H};
        cuuint64_t strides[4] = {(cuuint64_t)CH * 2, (cuuint64_t)CH * 2 * 4, (cuuint64_t)CH * 2 * 2,
                                 (cuuint64_t)IMG_W * CH * 2};
        cuuint32_t box[5] = {16, 2, 18, 2, 1};
        encode(&xmap, CU_TENSOR_MAP_DATA_TYPE_BFLOAT16, 5, d_in[0], dims, strides, box, estr5,
               CU_TENSOR_MAP_INTERLEAVE_NONE, CU_TENSOR_MAP_SWIZZLE_32B, PROMO,
               CU_TENSOR_MAP_FLOAT_OOB_FILL_NONE);
        box[0] = 32;
        encode(&xm.m[1], CU_TENSOR_MAP_DATA_TYPE_BFLOAT16, 5, d_in[0], dims, strides, box, estr5,
               CU_TENSOR_MAP_INTERLEAVE_NONE, CU_TENSOR_MAP_SWIZZLE_64B, PROMO,
               CU_TENSOR_MAP_FLOAT_OOB_FILL_NONE);
    }
    {
        cuuint64_t dims[5] = {32, 2, (cuuint64_t)IMG_H * IMG_W / 4, 3, 2};
        cuuint64_t strides[4] = {(cuuint64_t)CH * 2, (cuuint64_t)CH * 2 * 4, 64, (cuuint64_t)CH * 2 * 2};
        cuuint32_t box[5] = {32, 2, 16, 3, 1};
        encode(&omap, CU_TENSOR_MAP_DATA_TYPE_BFLOAT16, 5, d_out, dims, strides, box, estr5,
               CU_TENSOR_MAP_INTERLEAVE_NONE, CU_TENSOR_MAP_SWIZZLE_NONE, CU_TENSOR_MAP_L2_PROMOTION_NONE,
               CU_TENSOR_MAP_FLOAT_OOB_FILL_NONE);
    }
    conv_kernel<<<NUM_CTAS, 384, SMEM_BYTES>>>(xm, omap, (const char*)d_in[1], (const char*)d_in[0]);
}
```

```cpp
#include <cuda_runtime.h>
#include <cuda_bf16.h>
#include <cuda.h>
#include <stdint.h>

namespace {

#define PFIRST
#define GAPB 2
#define PKH0 3
#define PKH1 PKH0
#define PKH (RANK == 0 ? PKH0 : PKH1)
#define KPS0 2
#define KPS1 KPS0
#define KPS (RANK == 0 ? KPS0 : KPS1)
#define EPK0 11
#define EPK1 EPK0
#define EPK (RANK == 0 ? EPK0 : EPK1)
#define SPK0 15
#define SPK1 SPK0
#define SPK (RANK == 0 ? SPK0 : SPK1)
#define KPE 0
#define HKS 3
#define ST_EF
#define PF 6
#define PF0 5
#define EQ0 0x7fa
#define EQ1 0x7fe
#define PLA0 0xf0223445566ff045ull
#define PLA1 0xff012445566ff045ull
#define PLB0 0x4444459aab000000ull
#define PLB1 0x4444459aab000000ull
#define FMODE0 1
#define FMODE1 1
#define ORD 0
#define FMODE (RANK == 0 ? FMODE0 : FMODE1)
#define LT0 0
#define LT1 0
#define LATE(n) (((RANK == 0 ? LT0 : LT1) >> (n)) & 1)
#define LL0 0x10
#define LL1 0x10
#define LLATE(n) (((RANK == 0 ? LL0 : LL1) >> (n)) & 1)
#define PO0 0x012654
#define PO1 PO0
#define PG(g) (((RANK == 0 ? PO0 : PO1) >> (20 - (g) * 4)) & 7)
#define M1FIRST (PG(2) >= 4 ? PG(2) & 3 : PG(3) & 3)
#define EBSLOT (PG(2) == 2 ? 8 : PG(3) == 2 ? 9 : 10)
#define NW0 0
#define NW1 NW0
#define NW(n) (((RANK == 0 ? NW0 : NW1) >> (n)) & 1)
#define DEC 1
#define RORD 0x675231
#define PW0 0
#define PW1 1
#define EPO 0x8c04ab9231ull
#define PROMO CU_TENSOR_MAP_L2_PROMOTION_L2_128B
#define ZEND 1
#define HPIN 0
#define LL2 0x20
#define LLATE2(n) ((LL2 >> (n)) & 1)
#define CPT 0x01234
#define CP(k) ((CPT >> (16 - 4 * (k))) & 7)
#define MEF 0
#define DEFW 0
#define PKSLOT 7
#define EQ(n) (((RANK == 0 ? EQ0 : EQ1) >> (n)) & 1)
#define LAG0 6
#define LEAD0 9
#define LAG1 LAG0
#define LEAD1 LEAD0
#define LAGPOS (RANK == 0 ? LAG0 : LAG1)
#define LEADPOS (RANK == 0 ? LEAD0 : LEAD1)
#define LAGK (LEADPOS > 20 ? 1 : LEADPOS >= 12 || LEADPOS < LAGPOS ? 2 : 1)
#define SEND1 4
#define SEND2 6
#define TL(slot)
#define TLC(slot)
constexpr int IMG_H = 512, IMG_W = 512, CH = 96;
constexpr int IN_SLAB = 72 * 32;
constexpr int IN_ROW = 3 * IN_SLAB;
constexpr int SL0 = 0, SL4 = IN_SLAB, SL2 = 2 * IN_SLAB, SL3 = 3 * IN_SLAB, IN_B = 8 * IN_SLAB;
constexpr int W_K8 = 3 * 512;
constexpr int W_TAP = 6 * W_K8;
constexpr int W_COMP = 3 * W_TAP;
constexpr int W_BYTES = 5 * W_COMP;
constexpr int X_CH = 32 * 64;
constexpr int X_UNIT = 3 * X_CH;
constexpr int X_BYTES = 3 * X_UNIT;
constexpr int X_TX = X_UNIT;
constexpr int SEG = 32;
constexpr int NIT = 11;
constexpr int NUM_CTAS = 128;
#define LAY 3
constexpr int OFF_W = LAY == 0 ? 0 : LAY == 1 ? 2 * X_BYTES : LAY == 2 ? 2 * X_BYTES + 8 * IN_ROW : 8 * IN_ROW;
constexpr int OFF_X = LAY == 0 ? W_BYTES : LAY == 3 ? W_BYTES + 8 * IN_ROW : 0;
constexpr int OFF_IN = LAY == 3 ? 0 : LAY == 2 ? 2 * X_BYTES : W_BYTES + 2 * X_BYTES;
constexpr int OFF_BAR = W_BYTES + 2 * X_BYTES + 8 * IN_ROW;
constexpr int SMEM_BYTES = 1024 + OFF_BAR + 1024;
static_assert(SMEM_BYTES <= 232448, "smem");
#define RDEL 400
constexpr uint32_t ROW_DELAY = RDEL;
constexpr int B_FULL0 = 0, B_FULLA = 8, B_FULLB = 16, B_FULLC = 24, B_EMPTYE = 32, B_EMPTYF = 40, B_EMPTYB = 48, B_HFULL = 56,
              B_FFULL = 64, B_SH = 72, B_SF = 80;

__device__ __forceinline__ uint32_t smem_u32(const void* p) {
    return (uint32_t)__cvta_generic_to_shared(p);
}
__device__ __forceinline__ void mbar_init(uint32_t bar, uint32_t count) {
    asm volatile("mbarrier.init.shared::cta.b64 [%0], %1;" ::"r"(bar), "r"(count) : "memory");
}
__device__ __forceinline__ void mbar_expect_tx(uint32_t bar, uint32_t bytes) {
    asm volatile("mbarrier.arrive.expect_tx.shared::cta.b64 _, [%0], %1;" ::"r"(bar), "r"(bytes) : "memory");
}
__device__ __forceinline__ void mbar_arrive(uint32_t bar) {
    asm volatile("mbarrier.arrive.shared::cta.b64 _, [%0];" ::"r"(bar) : "memory");
}
__device__ __forceinline__ void mbar_arrive_warp(uint32_t bar) {
    __syncwarp();
    asm volatile("{\n\t.reg .pred p;\n\telect.sync _|p, 0xffffffff;\n\t@p mbarrier.arrive.shared::cta.b64 _, [%0];\n\t}" ::"r"(bar) : "memory");
}
__device__ __forceinline__ void mbar_arrive_remote(uint32_t rbar) {
    asm volatile("mbarrier.arrive.relaxed.cluster.shared::cluster.b64 _, [%0];" ::"r"(rbar) : "memory");
}
__device__ __forceinline__ void mbar_expect_tx_remote(uint32_t rbar, uint32_t bytes) {
    asm volatile("mbarrier.arrive.expect_tx.relaxed.cluster.shared::cluster.b64 _, [%0], %1;" ::"r"(rbar), "r"(bytes) : "memory");
}
__device__ __forceinline__ void mbar_wait(uint32_t bar, uint32_t parity) {
    uint32_t done;
    for (;;) {
        asm volatile(
            "{\n\t.reg .pred p;\n\t"
            "mbarrier.try_wait.parity.shared::cta.b64 p, [%1], %2;\n\t"
            "selp.u32 %0, 1, 0, p;\n\t}"
            : "=r"(done) : "r"(bar), "r"(parity) : "memory");
        if (done) return;
    }
}
#define STAMP(t, j)
__device__ __forceinline__ uint32_t mbar_try(uint32_t bar, uint32_t parity) {
    uint32_t done;
    asm volatile("{\n\t.reg .pred p;\n\tmbarrier.try_wait.parity.shared::cta.b64 p, [%1], %2;\n\tselp.u32 %0, 1, 0, p;\n\t}"
                 : "=r"(done) : "r"(bar), "r"(parity) : "memory");
    return done;
}
#define HSL 0
__device__ __forceinline__ void mbar_wait_h(uint32_t bar, uint32_t parity) {
    mbar_wait(bar, parity);
}
__device__ __forceinline__ bool elect() {
    uint32_t el;
    asm volatile("{\n\t.reg .pred p;\n\telect.sync _|p, 0xffffffff;\n\tselp.u32 %0, 1, 0, p;\n\t}" : "=r"(el));
    return el;
}
__device__ __forceinline__ uint32_t mapa(uint32_t addr, uint32_t rank) {
    uint32_t r;
    asm("mapa.shared::cluster.u32 %0, %1, %2;" : "=r"(r) : "r"(addr), "r"(rank));
    return r;
}
__device__ __forceinline__ void tma_load_5d(uint32_t dst, const CUtensorMap* map, uint32_t bar,
                                            int c0, int c1, int c2, int c3, int c4, bool keep) {
    asm volatile(
        "cp.async.bulk.tensor.5d.shared::cluster.global.mbarrier::complete_tx::bytes "
        "[%0], [%1, {%3, %4, %5, %6, %7}], [%2];"
        ::"r"(dst), "l"((uint64_t)map), "r"(bar), "r"(c0), "r"(c1), "r"(c2), "r"(c3), "r"(c4) : "memory");
}
#define EFN 99
#define EFM 7
#define EFM2 0
#define EF(t, u) ((((t) < EFN ? EFM : EFM2) >> (u)) & 1)
__device__ __forceinline__ void tma_store_4d(const CUtensorMap* map, uint32_t src, int c0, int c1, int c2, int c3, bool ef) {
    uint64_t pol, pn;
    asm volatile("createpolicy.fractional.L2::evict_first.b64 %0, 1.0;" : "=l"(pol));
    asm volatile("createpolicy.fractional.L2::evict_normal.b64 %0, 1.0;" : "=l"(pn));
    if (!ef) pol = pn;
    asm volatile("cp.async.bulk.tensor.5d.global.shared::cta.bulk_group.L2::cache_hint [%0, {%2, %2, %3, %2, %4}], [%1], %5;"
                 ::"l"((uint64_t)map), "r"(src), "r"(c0), "r"(c3 * 128 + c1), "r"(c2), "l"(pol) : "memory");
}
__device__ __forceinline__ void load_row(uint32_t dst, uint32_t dstb, const CUtensorMap* xmap, uint32_t fb, int rank, int strip, int row, bool keep) {
    tma_load_5d(dst, xmap + 1, fb, rank * 64, 0, strip * 16 - 1, 0, row, keep);
    tma_load_5d(dstb, xmap, fb, 32 + rank * 16, 0, strip * 16 - 1, 0, row, keep);
}

__device__ __forceinline__ void wgmma_fence() { asm volatile("wgmma.fence.sync.aligned;" ::: "memory"); }
__device__ __forceinline__ void wgmma_commit() { asm volatile("wgmma.commit_group.sync.aligned;" ::: "memory"); }
template <int N>
__device__ __forceinline__ void wgmma_wait() { asm volatile("wgmma.wait_group.sync.aligned %0;" ::"n"(N) : "memory"); }

template <int SA>
__device__ __forceinline__ void wgmma_m64n96k16(float (&d)[48], const uint32_t* a, uint64_t db, int scale_d) {
    asm volatile(
        "{\n\t.reg .pred p;\n\t"
        "setp.ne.b32 p, %53, 0;\n\t"
        "wgmma.mma_async.sync.aligned.m64n96k16.f32.bf16.bf16 "
        "{%0, %1, %2, %3, %4, %5, %6, %7, %8, %9, %10, %11, %12, %13, %14, %15, "
        " %16, %17, %18, %19, %20, %21, %22, %23, %24, %25, %26, %27, %28, %29, %30, %31, "
        " %32, %33, %34, %35, %36, %37, %38, %39, %40, %41, %42, %43, %44, %45, %46, %47}, "
        "{%48, %49, %50, %51}, %52, p, %54, 1, 1;\n\t}"
        : "+f"(d[0]), "+f"(d[1]), "+f"(d[2]), "+f"(d[3]), "+f"(d[4]), "+f"(d[5]), "+f"(d[6]), "+f"(d[7]),
          "+f"(d[8]), "+f"(d[9]), "+f"(d[10]), "+f"(d[11]), "+f"(d[12]), "+f"(d[13]), "+f"(d[14]), "+f"(d[15]),
          "+f"(d[16]), "+f"(d[17]), "+f"(d[18]), "+f"(d[19]), "+f"(d[20]), "+f"(d[21]), "+f"(d[22]), "+f"(d[23]),
          "+f"(d[24]), "+f"(d[25]), "+f"(d[26]), "+f"(d[27]), "+f"(d[28]), "+f"(d[29]), "+f"(d[30]), "+f"(d[31]),
          "+f"(d[32]), "+f"(d[33]), "+f"(d[34]), "+f"(d[35]), "+f"(d[36]), "+f"(d[37]), "+f"(d[38]), "+f"(d[39]),
          "+f"(d[40]), "+f"(d[41]), "+f"(d[42]), "+f"(d[43]), "+f"(d[44]), "+f"(d[45]), "+f"(d[46]), "+f"(d[47])
        : "r"(a[0]), "r"(a[1]), "r"(a[2]), "r"(a[3]), "l"(db), "r"(scale_d), "n"(SA));
}

template <int N>
__device__ __forceinline__ void fence_regs(float (&r)[N]) {
#pragma unroll
    for (int i = 0; i < N; ++i) asm volatile("" : "+f"(r[i])::"memory");
}

__device__ __forceinline__ uint32_t bf2_add(uint32_t a, uint32_t b) {
    uint32_t r;
    asm volatile("add.rn.bf16x2 %0, %1, %2;" : "=r"(r) : "r"(a), "r"(b));
    return r;
}
__device__ __forceinline__ uint32_t bf2_sub(uint32_t a, uint32_t b) {
    uint32_t r;
    asm volatile("sub.rn.bf16x2 %0, %1, %2;" : "=r"(r) : "r"(a), "r"(b));
    return r;
}
template <uint32_t B>
__device__ __forceinline__ uint32_t bf2_fma(uint32_t a, uint32_t cc) {
    uint32_t r;
    asm volatile("fma.rn.bf16x2 %0, %1, %2, %3;" : "=r"(r) : "r"(a), "r"(B), "r"(cc));
    return r;
}
__device__ __forceinline__ uint32_t pack_bf16(float a, float b) {
    __nv_bfloat162 v = __floats2bfloat162_rn(a, b);
    return *reinterpret_cast<uint32_t*>(&v);
}

__device__ __forceinline__ uint32_t opaque_add(uint32_t a, uint32_t b) {
    uint32_t r;
    asm volatile("add.u32 %0, %1, %2;" : "=r"(r) : "r"(a), "r"(b));
    return r;
}
template <int K>
__device__ __forceinline__ void make_quads(uint32_t (&q)[12], const uint32_t (&x)[24], const uint32_t (&d2)[24],
                                           const uint32_t (&u)[24], int kc, uint32_t coef = 0) {
    uint32_t e[8];
#pragma unroll
    for (int i = 0; i < 8; ++i) e[i] = K == 1 ? bf2_add(x[kc * 8 + i], d2[kc * 8 + i]) : bf2_sub(x[kc * 8 + i], d2[kc * 8 + i]);
#pragma unroll
    for (int jj = 0; jj < 3; ++jj) {
        const int j = jj == 0 ? 1 : jj == 1 ? 0 : 2;
#pragma unroll
        for (int hl = 0; hl < 2; ++hl) {
#pragma unroll
            for (int h = 0; h < 2; ++h) {
                const int i = ((j + h) >> 1) * 4 + hl * 2 + ((j + h) & 1);
                const uint32_t uu = u[kc * 8 + i];
                if (K < 0) asm volatile("fma.rn.bf16x2 %0, %1, %2, %3;" : "=r"(q[j * 4 + hl * 2 + h]) : "r"(uu), "r"(coef), "r"(e[i]));
                else q[j * 4 + hl * 2 + h] = K == 0 ? bf2_fma<0x3f003f00u>(uu, e[i]) : K == 1 ? bf2_sub(e[i], uu)
                                      : K == 2 ? bf2_fma<0x40404040u>(e[i], uu) : bf2_fma<0xc000c000u>(uu, e[i]);
            }
        }
    }
}
template <bool MAKE_U, bool TIE>
__device__ __forceinline__ void make_mid(uint32_t (&q)[12], uint32_t (&d1)[24], const uint32_t (&d2)[24], uint32_t (&u)[24], int kc,
                                         const uint32_t (&d3)[24], uint32_t wg) {
    uint32_t y[8];
#pragma unroll
    for (int i = 0; i < 8; ++i) {
        y[i] = bf2_sub(d2[kc * 8 + i], d3[kc * 8 + i]);
        if (MAKE_U) asm volatile("sub.rn.bf16x2 %0, %0, %1;" : "+r"(u[kc * 8 + i]) : "r"(d1[kc * 8 + i]));
        if (TIE) asm volatile("{\n\t.reg .pred q;\n\tsetp.ne.u32 q, %3, 7;\n\t@q fma.rn.bf16x2 %0, %0, %2, %1;\n\t}" : "+r"(d1[kc * 8 + i]) : "r"(y[i]), "r"(0x40004000u), "r"(wg));
        else asm volatile("fma.rn.bf16x2 %0, %0, %2, %1;" : "+r"(d1[kc * 8 + i]) : "r"(y[i]), "r"(0x40004000u));
    }
#pragma unroll
    for (int jj = 0; jj < 3; ++jj) {
        const int j = jj == 0 ? 1 : jj == 1 ? 0 : 2;
#pragma unroll
        for (int hl = 0; hl < 2; ++hl) {
#pragma unroll
            for (int h = 0; h < 2; ++h) {
                const int i = ((j + h) >> 1) * 4 + hl * 2 + ((j + h) & 1);
                q[j * 4 + hl * 2 + h] = bf2_fma<0x3fc03fc0u>(y[i], u[kc * 8 + i]);
            }
        }
    }
}

struct Ctx {
    uint32_t bar;
    uint32_t wdesc;
    uint32_t wready, wg, tlo, k, zero, tlo2, vz, ua;
    int rk;
    uint32_t ld0, ld1;
    uint32_t xbuf;
    uint32_t r_off;
};

__device__ __forceinline__ void sb(const Ctx& c) {
    asm volatile("{\n\t.reg .pred q;\n\tsetp.eq.u32 q, %1, 7;\n\t@q mov.u32 %0, %clock;\n\t}" : "+r"(const_cast<Ctx&>(c).vz) : "r"(c.wg) : "memory");
}
__device__ __forceinline__ void sbz(const Ctx& c) {
    asm volatile("{\n\t.reg .pred q;\n\tsetp.eq.u32 q, %1, 7;\n\t@q mov.u32 %0, %clock;\n\t}" : "+r"(const_cast<Ctx&>(c).zero) : "r"(c.wg) : "memory");
}
#define FTW(n)
#define FTM
__device__ __forceinline__ void sbk(Ctx& c) {
    asm volatile("{\n\t.reg .pred q;\n\tsetp.eq.u32 q, %1, 7;\n\t@q mov.u32 %0, %clock;\n\t}" : "+r"(c.k) : "r"(c.wg) : "memory");
}
template <int OFF>
__device__ __forceinline__ void ldsm(uint32_t* r, uint32_t a, uint32_t ua) {
    asm volatile("{\n\t.reg .u32 t;\n\tadd.u32 t, %4, %5;\n\tldmatrix.sync.aligned.m8n8.x4.shared.b16 {%0, %1, %2, %3}, [t + %6];\n\t}"
                 : "=r"(r[0]), "=r"(r[1]), "=r"(r[2]), "=r"(r[3]) : "r"(a), "r"(ua), "n"(OFF) : "memory");
}
template <bool PLUS>
__device__ __forceinline__ uint32_t addr2(uint32_t b, uint32_t t) {
    uint32_t r;
    if (PLUS) asm volatile("mad.lo.s32 %0, %1, 2, %2;" : "=r"(r) : "r"(b), "r"(t));
    else asm volatile("{\n\t.reg .s32 x;\n\tneg.s32 x, %2;\n\tmad.lo.s32 %0, %1, 2, x;\n\t}" : "=r"(r) : "r"(b), "r"(t));
    return r;
}
template <int SLOT, int KC>
__device__ __forceinline__ void ld_chunk_t(uint32_t (&r)[24], const Ctx& c, uint32_t ua, uint32_t ub) {
    if (KC == 2) {
        ldsm<SLOT>(&r[16], c.ld0, ub);
        ldsm<SLOT>(&r[20], c.ld1, ub);
    } else {
        ldsm<2 * SLOT + KC * 16>(&r[KC * 8], addr2<KC == 0>(c.ld0, c.vz), ua);
        ldsm<2 * SLOT + 16 - KC * 16>(&r[KC * 8 + 4], addr2<KC != 0>(c.ld1, c.vz), ua);
    }
}
#define ld_chunk(r, c, slot, kc) ld_chunk_t<slot, kc>(r, c, c.ua, 0)

__device__ __forceinline__ void mma3p(float (&acc)[48], const uint32_t* q0, const uint32_t* q1, const uint32_t* q2,
                                      const Ctx& c, int k, int kc, bool fresh) {
    uint32_t wd;
    asm volatile("mov.b32 %0, %1;" : "=r"(wd) : "r"(c.wdesc));
    wgmma_fence();
#pragma unroll
    for (int j = 0; j < 3; ++j) {
        const uint32_t lo = wd + (uint32_t)((CP(k) * W_COMP + j * W_TAP + (kc == 2 ? 4 - 4 * c.rk : kc + 2 * c.rk) * W_K8) >> 4);
        const uint32_t hi = (uint32_t)((kc == 2 ? W_K8 : 2 * W_K8) >> 4) | (2u << 30);
        uint64_t db;
        asm("mov.b64 %0, {%1, %2};" : "=l"(db) : "r"(lo), "r"(hi));
        if (k == 3 && c.rk == 1) wgmma_m64n96k16<-1>(acc, j == 0 ? q0 : j == 1 ? q1 : q2, db, (fresh && j == 0) ? 0 : 1);
        else wgmma_m64n96k16<1>(acc, j == 0 ? q0 : j == 1 ? q1 : q2, db, (fresh && j == 0) ? 0 : 1);
    }
    wgmma_commit();
}
__device__ __forceinline__ void mma3(float (&acc)[48], const uint32_t (&q)[12], const Ctx& c, int k, int kc, bool fresh) {
    mma3p(acc, &q[0], &q[4], &q[8], c, k, kc, fresh);
}
__device__ __forceinline__ void make_dup(uint32_t (&q)[12], const uint32_t (&u)[24], const Ctx& c, int kc) {
#pragma unroll
    for (int i = 0; i < 4; ++i)
        q[kc * 4 + i] = opaque_add(u[kc * 8 + (i & 1) * 3 + (i >> 1) * 2 + 1], c.zero);
}
__device__ __forceinline__ void mma3d(float (&acc)[48], const uint32_t (&u)[24], const uint32_t (&q)[12], const Ctx& c, int k, int kc, int first = 0) {
    mma3p(acc, &u[kc * 8], &q[kc * 4], &u[kc * 8 + 4], c, k, kc, kc == first);
}
__device__ __forceinline__ void mma3u(float (&acc)[48], const uint32_t (&u)[24], uint32_t (&q)[12], const Ctx& c, int kc) {
    make_dup(q, u, c, kc);
    mma3d(acc, u, q, c, 3, kc);
}

__device__ __forceinline__ uint32_t pack_word(const float (&acc)[48], int i, int m) {
    const int o = ((i % 3) * 4 + m) * 4 + (i / 3) * 2;
    return pack_bf16(acc[o], acc[o + 1]);
}
__device__ __forceinline__ void st_async(uint32_t addr, uint32_t r0, uint32_t r1, uint32_t r2, uint32_t r3, uint32_t rbar) {
    asm volatile("st.async.weak.shared::cluster.mbarrier::complete_tx::bytes.v4.b32 [%0], {%1, %2, %3, %4}, [%5];"
                 ::"r"(addr), "r"(r0), "r"(r1), "r"(r2), "r"(r3), "r"(rbar) : "memory");
}
template <int I>
__device__ __forceinline__ void send_acc(float (&acc)[48], uint32_t (&kp)[24], const Ctx& c, int n, int at, int spk) {
    if (n == (at < spk ? at : spk)) {
        fence_regs(acc);
#pragma unroll
        for (int m = 0; m < 4; ++m) {
            if (at > spk) asm volatile("add.rn.bf16x2 %0, %0, %1;" : "+r"(kp[I * 4 + m]) : "r"(pack_word(acc, I, m)));
            else kp[I * 4 + m] = GAPB == 2 ? bf2_add(pack_word(acc, I, m), kp[I * 4 + m]) : pack_word(acc, I, m);
        }
    }
    if (n != at) return;
    const uint32_t ro = c.r_off + (c.zero >> n), rx = c.xbuf + ro, rb = c.bar + B_FFULL + ro;
    st_async(rx + (I / 3) * X_UNIT + (I % 3) * X_CH, kp[I * 4], kp[I * 4 + 1], kp[I * 4 + 2], kp[I * 4 + 3], rb);
}
template <int I, bool H = true>
__device__ __forceinline__ void send_half(const uint32_t (&p)[12], const Ctx& c, int n = 0) {
    const uint32_t ro = c.r_off + (c.zero >> n), rx = c.xbuf + ro, rb = c.bar + (H ? B_HFULL : B_FFULL) + ro;
    st_async(rx + (H ? 2 * X_UNIT : 0) + I * X_CH, p[I * 4], p[I * 4 + 1], p[I * 4 + 2], p[I * 4 + 3], rb);
}
template <int I0, int N>
__device__ __forceinline__ void fin_pack(float (&acc)[48], uint32_t (&pk)[N * 4]) {
    fence_regs(acc);
#pragma unroll
    for (int i = 0; i < N * 4; ++i) {
        pk[i] = pack_word(acc, I0 + (i >> 2), i & 3);
        asm volatile("" : "+r"(pk[i]));
    }
}
template <int N>
__device__ __forceinline__ void fin_load(uint32_t (&v)[N * 4], const Ctx& c, int off) {
#pragma unroll
    for (int i = 0; i < N; ++i)
        asm volatile("ld.shared.v4.b32 {%0, %1, %2, %3}, [%4];"
                     : "=r"(v[i * 4 + 0]), "=r"(v[i * 4 + 1]), "=r"(v[i * 4 + 2]), "=r"(v[i * 4 + 3])
                     : "r"(c.xbuf + off + (i / 3) * X_UNIT + (i % 3) * X_CH) : "memory");
}
template <int N>
__device__ __forceinline__ void fin_store(uint32_t (&pk)[N * 4], const uint32_t (&v)[N * 4], const Ctx& c, int off, int sbar) {
#pragma unroll
    for (int i = 0; i < N; ++i) {
#pragma unroll
        for (int j = i * 4; j < i * 4 + 4; ++j) asm volatile("add.rn.bf16x2 %0, %0, %1;" : "+r"(pk[j]) : "r"(v[j]));
        asm volatile("st.shared.v4.b32 [%0], {%1, %2, %3, %4};"
                     ::"r"(c.xbuf + off + (i / 3) * X_UNIT + (i % 3) * X_CH), "r"(pk[i * 4]), "r"(pk[i * 4 + 1]), "r"(pk[i * 4 + 2]),
                       "r"(pk[i * 4 + 3]) : "memory");
    }
    if (sbar >= 0) mbar_arrive_warp(c.bar + sbar);
}

__device__ __forceinline__ void pin(const uint32_t* r, const Ctx& c) {
    asm volatile("{\n\t.reg .pred q;\n\tsetp.ne.u32 q, %12, 7;\n\t@q bra.uni PIN_SKIP;\n\t"
                 "st.volatile.shared.v4.b32 [%13], {%0, %1, %2, %3};\n\tst.volatile.shared.v4.b32 [%13], {%4, %5, %6, %7};\n\t"
                 "st.volatile.shared.v4.b32 [%13], {%8, %9, %10, %11};\n\tPIN_SKIP:\n\t}"
                 ::"r"(r[0]), "r"(r[1]), "r"(r[2]), "r"(r[3]), "r"(r[4]), "r"(r[5]), "r"(r[6]), "r"(r[7]), "r"(r[8]), "r"(r[9]),
                   "r"(r[10]), "r"(r[11]), "r"(c.wg), "r"(c.bar) : "memory");
}
__device__ __forceinline__ void pin4(const uint32_t* r, const Ctx& c) {
    asm volatile("{\n\t.reg .pred q;\n\tsetp.eq.u32 q, %4, 7;\n\t@q st.volatile.shared.v4.b32 [%5], {%0, %1, %2, %3};\n\t}"
                 ::"r"(r[0]), "r"(r[1]), "r"(r[2]), "r"(r[3]), "r"(c.wg), "r"(c.bar) : "memory");
}
__device__ __forceinline__ void acc_add(float& d, float x, float k) {
    asm volatile("fma.rn.f32 %0, %1, %2, %0;" : "+f"(d) : "f"(x), "f"(k));
}
__device__ __forceinline__ void acc_scale_add(float& d, float k, float x) {
    asm volatile("fma.rn.f32 %0, %0, %2, %1;" : "+f"(d) : "f"(x), "f"(k));
}
template <int RANK, int I0 = 0, int I1 = 24>
__device__ __forceinline__ void mid_row(float (&b)[48], const float (&k)[48], uint32_t (&ps)[12], uint32_t (&pk)[12],
                                        float f = -2.f) {
#pragma unroll
    for (int i = I0; i < I1; ++i) {
        const int ch = i >> 2, o = ((ch % 3) * 4 + (i & 3)) * 4 + (ch / 3) * 2;
        acc_scale_add(b[o], f, k[o]);
        acc_scale_add(b[o + 1], f, k[o + 1]);
        uint32_t& dst = (i / 12 == RANK) ? pk[i % 12] : ps[i % 12];
        dst = pack_bf16(b[o], b[o + 1]);
        asm volatile("" : "+r"(dst));
    }
}
template <int RANK>
__device__ __forceinline__ void mid_row2(float (&b)[48], const float (&k)[48], uint32_t (&ps)[12], uint32_t (&pk)[12], uint32_t (&kp)[24]) {
#pragma unroll
    for (int j = 0; j < 24; ++j) {
        const int i = EPK & 16 ? (j >> 1) + 12 * (j & 1) : (j + 12 - 12 * RANK) % 24;
        const int ch = i >> 2, o = ((ch % 3) * 4 + (i & 3)) * 4 + (ch / 3) * 2;
        const bool keep = i / 12 == RANK;
        uint32_t& dst = keep ? pk[i % 12] : ps[i % 12];
        if (!((PKH >> (keep ? 0 : 1)) & 1)) {
            acc_scale_add(b[o], -2.f, k[o]);
            acc_scale_add(b[o + 1], -2.f, k[o + 1]);
        }
        if (!((PKH & EPK) >> (keep ? 0 : 1) & 1)) dst = pack_bf16(b[o], b[o + 1]);
        if (!keep && (PKH & 2)) {
            kp[i] = pack_bf16(k[o], k[o + 1]);
            asm volatile("" : "+r"(kp[i]));
            dst = bf2_fma<0xc000c000u>(dst, kp[i]);
        }
        asm volatile("" : "+r"(dst));
    }
}
template <int RANK>
__device__ __forceinline__ void pack_k(const float (&k)[48], uint32_t (&kp)[24]) {
#pragma unroll
    for (int i = 0; i < 24; ++i) {
        if (i / 12 != RANK && (PKH & 2)) continue;
        kp[i] = pack_word(k, i >> 2, i & 3);
        asm volatile("" : "+r"(kp[i]));
    }
}
template <int RANK>
__device__ __forceinline__ void fix_hk(uint32_t (&hk)[12], const uint32_t (&kp)[24]) {
    if (PKH & 1) {
#pragma unroll
        for (int i = 0; i < 12; ++i) asm volatile("fma.rn.bf16x2 %0, %0, %2, %1;" : "+r"(hk[i]) : "r"(kp[RANK * 12 + i]), "r"(0xc000c000u));
    }
}
template <int I0, int I1>
__device__ __forceinline__ void acc_add_n(float (&d)[48], const float (&x)[48], float k) {
#pragma unroll
    for (int i = I0; i < I1; ++i) acc_add(d[i], x[i], k);
}

template <int RANK, bool LAST, int I0, int I1>
__device__ __forceinline__ void acc_add_pk(float (&d)[48], const float (&x)[48], float k, uint32_t (&ps)[12], uint32_t (&pk)[12]) {
    if (LAST || !(EPK & 3)) { acc_add_n<I0, I1>(d, x, k); return; }
#pragma unroll
    for (int j = I0 / 2; j < I1 / 2; ++j) {
        const int i = EPK & 8 ? (j >> 1) + 12 * (j & 1) : (j + 12 * ((EPK >> 2 ^ RANK) & 1)) % 24;
        const int ch = i >> 2, o = ((ch % 3) * 4 + (i & 3)) * 4 + (ch / 3) * 2;
        const bool keep = i / 12 == RANK;
        uint32_t& dst = keep ? pk[i % 12] : ps[i % 12];
        acc_add(d[o], x[o], k);
        acc_add(d[o + 1], x[o + 1], k);
        if ((PKH & EPK) >> (keep ? 0 : 1) & 1) {
            dst = pack_bf16(d[o], d[o + 1]);
            asm volatile("" : "+r"(dst));
        }
    }
}

#define LOCK 1
__device__ __forceinline__ void stagger_lead(const Ctx& c, uint32_t id) {
    if (LOCK) {
        asm volatile("{\n\t.reg .pred p;\n\tsetp.eq.u32 p, %1, 0;\n\t@p bar.sync %0, 256;\n\t}" ::"r"(id), "r"(c.wg) : "memory");
        return;
    }
    asm volatile("{\n\t.reg .pred p;\n\tsetp.eq.u32 p, %1, 0;\n\t@p bar.arrive %0, 256;\n\t}" ::"r"(id), "r"(c.wg) : "memory");
}
__device__ __forceinline__ void stagger_lag(const Ctx& c, uint32_t id) {
    asm volatile("{\n\t.reg .pred p;\n\tsetp.ne.u32 p, %1, 0;\n\t@p bar.sync %0, 256;\n\t}" ::"r"(id), "r"(c.wg) : "memory");
}

#define DEFM 0
#define M1O 0x012
#define M1O0 M1O
#define MO(i) (((RANK == 0 ? M1O0 : M1O) >> (8 - 4 * (i))) & 3)
#define QHW 1
#define CPY 0
#define LDP 0
#define DUPL 0
#define PQ0 0
#define PQ1 0
#define TIE0 0
#define TIE1 0
#define WA 0
#define WB 0
#define PKF (AT(23) == PKSLOT)
#define PROBE 0
#define PAPOS 0
#define PPOS 1
#define CS1 16
#define EPI 0
#define FT_BASE 538
template <int RANK, bool LAST>
__device__ __forceinline__ void phase1b(Ctx& c, float (&accS)[48], float (&accK)[48], float (&accC)[48],
                                        uint32_t (&d0)[24], uint32_t (&d1)[24], const uint32_t (&d2)[24],
                                        const uint32_t (&u)[24], uint32_t (&qd)[12], uint32_t (&qh)[12],
                                        uint32_t (&hs)[12], uint32_t (&hk)[12]) {
    uint32_t pa_ = 0;
    if ((PROBE & 1) && PAPOS == 0) pa_ = mbar_try(c.bar + B_FULLA, LAST ? (NIT - 1) & 1 : c.k & 1);
    fence_regs(accS);
    fence_regs(accC);
#pragma unroll
    for (int i = 0; i < 48; ++i)
        asm volatile("fma.rn.f32 %0, %1, %2, %3;" : "=f"(accK[i]) : "f"(accS[i]), "f"(RANK == 0 ? 1.f / 3.f : -4.f / 3.f), "f"(accC[i]));
    constexpr float CF = RANK == 0 ? -1.f / 6.f : -1.f / 3.f;
    if (DUPL) make_dup(qd, d1, c, MO(0));
    mma3d(accK, d1, qd, c, 1, MO(0), -1);
    sb(c);
    if ((PROBE & 1) && PAPOS == 1) pa_ = mbar_try(c.bar + B_FULLA, LAST ? (NIT - 1) & 1 : c.k & 1);
    if (!LAST && LEADPOS == 12) stagger_lead(c, c.k + 1);
    make_dup(qd, d1, c, MO(1));
    mma3d(accK, d1, qd, c, 1, MO(1), -1);
    sb(c);
    if ((PROBE & 1) && PAPOS == 2) pa_ = mbar_try(c.bar + B_FULLA, LAST ? (NIT - 1) & 1 : c.k & 1);
    if (!LAST && LEADPOS == 13) stagger_lead(c, c.k + 1);
    acc_add_pk<RANK, LAST, 0, CS1>(accC, accS, CF, hs, hk);
    if (PROBE & 16) sb(c);
    if (__builtin_expect(!pa_, PROBE & 1 ? 0 : 1)) mbar_wait(c.bar + B_FULLA, LAST ? (NIT - 1) & 1 : c.k & 1);
    if (WA == 1 && !LAST && c.k == 0) mbar_wait(c.bar + B_FULLA, 0);
    if (WA) sb(c);
    wgmma_wait<1>();
    if (LDP == 1) sb(c);
    if (LDP < 2) {
        if (RANK == 0 && !LAST) ld_chunk(d1, c, SL4, 0);
        else ld_chunk(d0, c, SL0, 0);
    }
    make_dup(qd, d1, c, MO(2));
    mma3d(accK, d1, qd, c, 1, MO(2), -1);
    sb(c);
    if (!LAST && LEADPOS == 14) stagger_lead(c, c.k + 1);
    if (LDP == 2) {
        if (RANK == 0 && !LAST) ld_chunk(d1, c, SL4, 0);
        else ld_chunk(d0, c, SL0, 0);
    }
    if (LAST && (EPI & 2)) ld_chunk(d0, c, SL0, 1);
    acc_add_pk<RANK, LAST, CS1, 48>(accC, accS, CF, hs, hk);
    sb(c);
    wgmma_wait<QHW>();
    if (LDP == 3) {
        if (RANK == 0 && !LAST) ld_chunk(d1, c, SL4, 0);
        else ld_chunk(d0, c, SL0, 0);
    }
    if (LAST && (EPI & 1) && !(EPI & 2)) ld_chunk(d0, c, SL0, 1);
    if (LAST && (EPI & 1)) { ld_chunk(d0, c, SL0, 2); sb(c); }
    if (RANK == 0 && !LAST) make_quads<4>(qh, d1, d2, u, 0);
    else make_quads<0>(qh, d0, d2, u, 0);
    sb(c);
}

#define WFA 1
#define P1MC 1
#define P2MC 6
#define WF1C 0
template <int RANK>
__device__ __forceinline__ void consumer(Ctx& c) {
    float accS[48], accK[48], accC[48];
    uint32_t d0[24], d1[24], d2[24], u[24];
    uint32_t qd[12];
#pragma unroll
    for (int i = 0; i < 48; ++i) { accS[i] = 0.f; accC[i] = 0.f; }
    {
        uint32_t qa[12], qe[12];
#define PRO 126
        if ((PRO & 1) || ((PRO & 32) && c.wg)) {
            mbar_wait(c.wready, 0);
            if (!WF1C) asm volatile("fence.proxy.async.shared::cta;" ::: "memory");
            TL(18);
        }
        mbar_wait(c.bar + B_FULL0, 0);
        c.rk = RANK;
        sbz(c);
        const uint32_t xo = (uint32_t)(OFF_X - OFF_IN) - c.wg * (4 * IN_ROW - X_BYTES);
        uint32_t (&d3)[24] = PRO & 4 ? d0 : u;
        ld_chunk_t<0, 0>(d1, c, c.ua + xo, 0);
        ld_chunk(d3, c, SL3, 0);
#define PLD 1
        if (PLD < 2) {
            ld_chunk_t<0, 1>(d1, c, c.ua + xo, 0);
            ld_chunk(d3, c, SL3, 1);
        }
        if (PLD < 1) {
            ld_chunk_t<0, 2>(d1, c, 0, xo + 2 * IN_SLAB - IN_B);
            ld_chunk(d3, c, SL3, 2);
        }
        if (PRO & 2) {
#pragma unroll
            for (int kc = 0; kc < 3; ++kc) {
                if (kc == 1 && PLD == 2) {
                    ld_chunk_t<0, 1>(d1, c, c.ua + xo, 0);
                    ld_chunk(d3, c, SL3, 1);
                }
                if (kc == 1 && PLD) {
                    ld_chunk_t<0, 2>(d1, c, 0, xo + 2 * IN_SLAB - IN_B);
                    ld_chunk(d3, c, SL3, 2);
                }
                if (kc == 2 && (PRO & 64)) {
                    mbar_wait(c.bar + B_FULLC, 0);
                    ld_chunk(d2, c, SL2, 0);
                }
#pragma unroll
                for (int i = kc * 8; i < kc * 8 + 8; ++i) u[i] = bf2_sub(d3[i], d1[i]);
                make_dup(qe, u, c, kc);
                if (kc == 0 && (PRO & 32) && !c.wg) {
                    TL(18);
                    mbar_wait(c.wready, 0);
                    asm volatile("fence.proxy.async.shared::cta;" ::: "memory");
                }
                if (kc == 0) TL(19);
                mma3d(accS, u, qe, c, 3, kc);
                sb(c);
            }
        } else {
#pragma unroll
            for (int i = 0; i < 24; ++i) u[i] = bf2_sub(d3[i], d1[i]);
#pragma unroll
            for (int kc = 0; kc < 3; ++kc) make_dup(qe, u, c, kc);
            if (!(PRO & 1)) {
                TL(18);
                mbar_wait(c.wready, 0);
                if (!WF1C) asm volatile("fence.proxy.async.shared::cta;" ::: "memory");
            }
            TL(19);
#pragma unroll
            for (int kc = 0; kc < 3; ++kc) mma3d(accS, u, qe, c, 3, kc);
        }
        if (!(PRO & 64)) mbar_wait(c.bar + B_FULLC, 0);
        if (!(P1MC & 2) && !(PRO & 8)) mbar_wait(c.wready + (P2MC ? 32 : 16), 0);
        if (!(PRO & 64)) ld_chunk(d2, c, SL2, 0);
        if (!(PRO & 4)) ld_chunk(d0, c, SL3, 0);
        ld_chunk(d2, c, SL2, 1);
        if (!(PRO & 4)) ld_chunk(d0, c, SL3, 1);
        else ld_chunk(d2, c, SL2, 2);
        if (!(P1MC & 2) && (PRO & 8)) mbar_wait(c.wready + (P2MC ? 32 : 16), 0);
#pragma unroll
        for (int kc = 0; kc < 3; ++kc) {
            if (kc == 1 && !(PRO & 4)) { sb(c); ld_chunk(d2, c, SL2, 2); ld_chunk(d0, c, SL3, 2); }
#pragma unroll
            for (int i = kc * 8; i < kc * 8 + 8; ++i) {
                asm volatile("sub.rn.bf16x2 %0, %1, %0;" : "+r"(d0[i]) : "r"(d2[i]));
                asm volatile("fma.rn.bf16x2 %0, %0, %2, %1;" : "+r"(d1[i]) : "r"(d0[i]), "r"(0x40004000u));
                asm volatile("fma.rn.bf16x2 %0, %0, %2, %1;" : "+r"(d0[i]) : "r"(u[i]), "r"(0x3fc03fc0u));
            }
            make_dup(qa, d0, c, kc);
            mma3d(accC, d0, qa, c, 2, kc);
            if (PRO & 16) sb(c);
        }
        mbar_arrive_warp(c.bar + B_EMPTYB);
        if (!DUPL) make_dup(qd, d1, c, MO(0));
        if (LAGK == 2) asm volatile("{\n\t.reg .pred p;\n\tsetp.ne.u32 p, %0, 0;\n\t@p bar.arrive 1, 256;\n\t}" ::"r"(c.wg) : "memory");
        if (WA == 2) mbar_wait(c.bar + B_FULLA, 0);
        if ((P2MC || (P1MC & 2)) && !WFA) mbar_wait(c.wready + 16, 0);
        wgmma_wait<0>();
        c.k = c.zero;
        TL(23);
    }
    constexpr int KA = RANK == 0 ? 4 : 0, KB = 4 - KA;
    constexpr int SA = RANK == 0 ? SL4 : SL0, SB = RANK == 0 ? SL0 : SL4;
    uint32_t (&ea)[24] = RANK == 0 ? d1 : d0;
    uint32_t (&eb)[24] = RANK == 0 ? d0 : d1;
#pragma unroll 1
    while (c.k < NIT - 1) {
#define par(n) ((c.k + (c.zero >> n)) & 1)
        uint32_t qa[12], qb[12], qe[12], qh[12], hs[12], hk[12];
        uint32_t hv[12], pa[12], pb[12], va[12], vb[12], kp[24], pb_ = 0, ph_ = 0, pf_ = 0;
        phase1b<RANK, false>(c, accS, accK, accC, d0, d1, d2, u, qd, qh, hs, hk);
#define AT(i) (int)(((RANK == 0 ? (i < 16 ? PLA0 : PLB0) : (i < 16 ? PLA1 : PLB1)) >> (60 - 4 * (i & 15))) & 15)
#define SLOT(n)                                                                                   \
        if (AT(2) == n && FMODE != 1) mbar_wait(c.bar + B_FULL0 + FMODE * 8, par(n));             \
        if (PPOS == 0) { PROBES(n) } if (AT(5) == n && __builtin_expect(!pb_, PROBE & 2 ? 0 : 1)) mbar_wait(c.bar + B_FULLB, par(n));                         \
        if (AT(14) == n && __builtin_expect(!ph_, PROBE & 4 ? 0 : 1)) mbar_wait(c.bar + B_HFULL, par(n));                                      \
        if (AT(22) == n && __builtin_expect(!pf_, PROBE & 8 ? 0 : 1)) mbar_wait(c.bar + B_FFULL, par(n));                                      \
        if (n == 2) mbar_arrive_warp(c.bar + B_EMPTYE);                                           \
        if (n == 5) mbar_arrive_warp(c.bar + B_EMPTYF);                                           \
        if (n == EBSLOT) mbar_arrive_warp(c.bar + B_EMPTYB);                                      \
        if (!LLATE(n)) { LOADS(n) }                                                               \
        if (!LATE(n)) { STORES(n) }                                                               \
        if (PPOS == 1) { PROBES(n) }
#define PROBES(n)                                                                                 \
        if ((PROBE & 2) && AT(5) == n + 1) pb_ = mbar_try(c.bar + B_FULLB, par(n));              \
        if ((PROBE & 4) && AT(14) == n + 1) ph_ = mbar_try(c.bar + B_HFULL, par(n));              \
        if ((PROBE & 8) && AT(22) == n + 1) pf_ = mbar_try(c.bar + B_FFULL, par(n));
#define LOADS(n)                                                                                  \
        if (AT(0) == n) ld_chunk(ea, c, SA, 1);                                                   \
        if (AT(1) == n) ld_chunk(ea, c, SA, 2);                                                   \
        if (AT(2) == n) ld_chunk(eb, c, SB, 0);                                                   \
        if (AT(3) == n) ld_chunk(eb, c, SB, 1);                                                   \
        if (AT(4) == n) ld_chunk(eb, c, SB, 2);                                                   \
        if (AT(5) == n) ld_chunk(u, c, SL3, 0);                                                   \
        if (AT(6) == n) ld_chunk(d2, c, SL2, 0);                                                  \
        if (AT(7) == n) ld_chunk(u, c, SL3, 1);                                                   \
        if (AT(8) == n) ld_chunk(d2, c, SL2, 1);                                                  \
        if (AT(9) == n) ld_chunk(u, c, SL3, 2);                                                   \
        if (AT(10) == n) ld_chunk(d2, c, SL2, 2);                                                 \
        if (AT(14) == n) fin_load<3>(hv, c, 2 * X_UNIT);                                          \
        if (AT(22) == n) fin_load<3>(va, c, 0);                                                   \
        if (AT(24) == n) fin_load<3>(vb, c, X_UNIT);
#define STORES(n)                                                                                 \
        if (n == PKSLOT && PKF) { fin_pack<0, 3>(accK, pa); fin_pack<3, 3>(accK, pb); if (AT(23) != n) pin(pa, c); if (AT(25) != n) pin(pb, c); } \
        if (AT(15) == n) fin_store<3>(hk, hv, c, 2 * X_UNIT, B_SH);                               \
        if (AT(23) == n) fin_store<3>(pa, va, c, 0, -1);                                          \
        if (AT(25) == n) fin_store<3>(pb, vb, c, X_UNIT, B_SF);                                   \
        if (LLATE(n) && !LLATE2(n)) { LOADS(n) }                                                  \
        if (AT(11) == n) send_half<0>(hs, c, n);                                                  \
        if (AT(12) == n) send_half<1>(hs, c, n);                                                  \
        if (AT(13) == n) send_half<2>(hs, c, n);                                                  \
        send_acc<0>(accS, kp, c, n, AT(16), SPK);                                          \
        send_acc<3>(accS, kp, c, n, AT(17), SPK);                                          \
        send_acc<1>(accS, kp, c, n, AT(18), SPK);                                          \
        send_acc<4>(accS, kp, c, n, AT(19), SPK);                                          \
        send_acc<2>(accS, kp, c, n, AT(20), SPK);                                          \
        send_acc<5>(accS, kp, c, n, AT(21), SPK);                                          \
        if (LLATE(n) && LLATE2(n)) { LOADS(n) }                                                   \
        if (n == PKSLOT && !PKF) { fin_pack<0, 3>(accK, pa); fin_pack<3, 3>(accK, pb); pin(pa, c); pin(pb, c); }
#define QW(n, Q)                                                                     \
        if (LATE(n)) { Q; sb(c); STORES(n); sb(c); wgmma_wait<1 + NW(n)>(); FTW(n); }        \
        else if (EQ(n)) { Q; sb(c); wgmma_wait<1 + NW(n)>(); FTW(n); } else { sb(c); wgmma_wait<1 + NW(n)>(); FTW(n); Q; } \
        if (PPOS == 2) { PROBES(n) }                                                              \
        if (LAGPOS == n) stagger_lag(c, c.k + LAGK);                                              \
        if (LEADPOS == n) stagger_lead(c, c.k + 1);
#define P1(g, q)                                                                                  \
        SLOT(g + 5);                                                                              \
        if (PG(g) < 4) {                                                                          \
            QW(g + 5, (make_mid<true, (((RANK == 0 ? TIE0 : TIE1) >> (PG(g) & 3)) & 1) != 0>(q, d1, d2, u, PG(g) & 3, u, c.wg)));                                 \
            mma3(accC, q, c, 2, PG(g) & 3, g == 0);                                               \
        } else {                                                                                  \
            QW(g + 5, make_dup(qe, u, c, PG(g) & 3));                                             \
            mma3d(accS, u, qe, c, 3, PG(g) & 3, M1FIRST);                                         \
        }
        if (!GAPB) {
            wgmma_wait<0>();
            fence_regs(accK);
            if (!DEFM) {
                mid_row<RANK>(accC, accK, hs, hk);
                pin(hk, c);
                SLOT(15);
            } else {
                LOADS(15);
            }
            sbk(c);
            acc_add_n<0, 48>(accS, accK, 1.f);
            mma3(accS, qh, c, KA, 0, false);
            sb(c);
            if (DEFM) {
                mid_row<RANK>(accC, accK, hs, hk);
                pin(hk, c);
                STORES(15);
                sb(c);
            }
        } else {
            mma3(accS, qh, c, KA, 0, false);
            wgmma_wait<1>();
            fence_regs(accK);
            LOADS(15);
            sbk(c);
            if (GAPB == 2) mid_row2<RANK>(accC, accK, hs, hk, kp);
            else mid_row<RANK>(accC, accK, hs, hk);
            pin(hk, c);
            STORES(15);
            sb(c);
        }
#define PK_(n, e) if (GAPB == 2 && KPS == n && KPE == e) pack_k<RANK>(accK, kp); if (GAPB == 2 && HKS == n && KPE == e) fix_hk<RANK>(hk, kp);
        PK_(0, 2)
        SLOT(0);
        PK_(0, 1)
        make_quads<KA>(qa, ea, d2, u, 1);
        PK_(0, 0)
        mma3(accS, qa, c, KA, 1, false);
        sb(c);
        PK_(1, 2)
        SLOT(1);
        PK_(1, 1)
        QW(1, make_quads<KA>(qb, ea, d2, u, 2); PK_(1, 0));
        mma3(accS, qb, c, KA, 2, false);
        sb(c);
        PK_(2, 2)
        SLOT(2);
        PK_(2, 1)
        QW(2, make_quads<KB>(qa, eb, d2, u, 0); PK_(2, 0));
        if (WB) mbar_wait(c.bar + B_FULLB, par(2));
        if (WB == 2) mbar_wait(c.bar + B_HFULL, par(2));
        if (GAPB == 1) {
            wgmma_wait<0>();
            fence_regs(accS);
            acc_add_n<0, 48>(accS, accK, 1.f);
        }
        mma3(accK, qa, c, KB, 0, false);
        sb(c);
        PK_(3, 2)
        SLOT(3);
        PK_(3, 1)
        QW(3, make_quads<KB>(qb, eb, d2, u, 1); PK_(3, 0));
        mma3(accK, qb, c, KB, 1, false);
        sb(c);
        PK_(4, 2)
        SLOT(4);
        QW(4, make_quads<KB>(qa, eb, d2, u, 2));
        mma3(accK, qa, c, KB, 2, false);
        sb(c);
        P1(0, qb);

        sb(c);
        P1(1, qa);

        sb(c);
        P1(2, qb);

        sb(c);
        P1(3, qa);

        sb(c);
        P1(4, qb);

        sb(c);
        P1(5, qa);

        sb(c);
        SLOT(11);
        if (LAGPOS == 11) stagger_lag(c, c.k + LAGK);
        if (LEADPOS == 11) stagger_lead(c, c.k + 1);
        if (!DUPL) make_dup(qd, d1, c, MO(0));
#pragma unroll
        for (int i = 0; i < 12; ++i)
            if (((RANK == 0 ? PQ0 : PQ1) >> i) & 1) pin4(&d2[(i % 6) * 4], c);
        sbz(c);
        ++c.k;
        if (WA) mbar_wait(c.bar + B_FULLA, c.k & 1);
        wgmma_wait<0>();
        TL(1 + c.k);
#undef par
    }
    {
        constexpr uint32_t par = (NIT - 1) & 1;
        uint32_t qa[12], qb[12], qh[12], hs[12], hk[12], v[12];
        constexpr int S0 = 12 - 12 * RANK, K0 = 12 * RANK;
        uint32_t pk[12];
        if (LAGK == 2) stagger_lead(c, NIT);
        phase1b<RANK, true>(c, accS, accK, accC, d0, d1, d2, u, qd, qh, hs, hk);
#define TE(n)
        TE(4);
        mma3(accS, qh, c, 0, 0, RANK == 0);
        if (EPI & 1) {
            sb(c);
            make_quads<0>(qa, d0, d2, u, 1);
            mma3(accS, qa, c, 0, 1, false);
            sb(c);
            make_quads<0>(qb, d0, d2, u, 2);
            mma3(accS, qb, c, 0, 2, false);
            wgmma_wait<3>();
            fence_regs(accK);
            mid_row<RANK, S0, S0 + 12>(accC, accK, hs, hk);
            send_half<0>(hs, c);
            send_half<1>(hs, c);
            send_half<2>(hs, c);
            sb(c);
        } else {
            wgmma_wait<1>();
            ld_chunk(d0, c, SL0, 1);
            ld_chunk(d0, c, SL0, 2);
            fence_regs(accK);
            mid_row<RANK, S0, S0 + 12>(accC, accK, hs, hk);
            send_half<0>(hs, c);
            send_half<1>(hs, c);
            send_half<2>(hs, c);
            sb(c);
            make_quads<0>(qa, d0, d2, u, 1);
            mma3(accS, qa, c, 0, 1, false);
            make_quads<0>(qb, d0, d2, u, 2);
            mma3(accS, qb, c, 0, 2, false);
        }
        TE(5);
        mid_row<RANK, K0, K0 + 12>(accC, accK, hs, hk);
        mbar_wait(c.bar + B_FULLB, par);
        TE(6);
        wgmma_wait<0>();
        TE(7);
        fence_regs(accS);
        mid_row<RANK, S0, S0 + 12>(accS, accK, hs, pk, 1.f);
        send_half<0, false>(hs, c);
        send_half<1, false>(hs, c);
        send_half<2, false>(hs, c);
        TE(8);
        mbar_wait(c.bar + B_HFULL, par);
        TE(9);
        fin_load<3>(v, c, 2 * X_UNIT);
        mid_row<RANK, K0, K0 + 12>(accS, accK, hs, pk, 1.f);
        fin_store<3>(hk, v, c, 2 * X_UNIT, B_SH);
        mbar_wait(c.bar + B_FFULL + c.zero, par);
        TE(10);
        fin_load<3>(v, c, 0);
        fin_store<3>(pk, v, c, 0, B_SF);
        TL(17);
    }
}

__device__ __forceinline__ void wt_load(uint32_t (&g)[36], uint32_t unit, int lane) {
    const uint32_t src = unit + (lane >> 2) * 192 + ((lane & 3) << 4);
#pragma unroll
    for (int i = 0; i < 9; ++i)
        asm volatile("ld.shared.v4.b32 {%0, %1, %2, %3}, [%4];"
                     : "=r"(g[i * 4]), "=r"(g[i * 4 + 1]), "=r"(g[i * 4 + 2]), "=r"(g[i * 4 + 3])
                     : "r"(src + (i / 3) * 64 + (i % 3) * 2 * W_COMP) : "memory");
}
__device__ __forceinline__ void stsm(uint32_t addr, const uint32_t* v) {
    asm volatile("stmatrix.sync.aligned.m8n8.x4.shared.b16 [%0], {%1, %2, %3, %4};"
                 ::"r"(addr), "r"(v[0]), "r"(v[1]), "r"(v[2]), "r"(v[3]) : "memory");
}
template <int PART>
__device__ __forceinline__ void wt_store(const uint32_t (&g)[36], uint32_t unit, int lane) {
    const uint32_t dst = unit + (lane & 7) * 64 + ((((lane >> 3) ^ (lane >> 1)) & 3) << 4);
#pragma unroll
    for (int r = 0; r < 3; ++r) {
        const uint32_t *a = &g[r * 12], *b = a + 4, *cc = a + 8;
        uint32_t u1[4], u2[4], u3[4];
#pragma unroll
        for (int i = 0; i < 4; ++i) {
            uint32_t h;
            asm("add.rn.bf16x2 %0, %1, %2;" : "=r"(h) : "r"(a[i]), "r"(cc[i]));
            asm("mul.rn.bf16x2 %0, %1, %2;" : "=r"(h) : "r"(h), "r"(0x3f003f00u));
            asm("fma.rn.bf16x2 %0, %1, %2, %3;" : "=r"(u1[i]) : "r"(b[i]), "r"(0x3f003f00u), "r"(h));
            asm("fma.rn.bf16x2 %0, %1, %2, %3;" : "=r"(u2[i]) : "r"(b[i]), "r"(0xbf00bf00u), "r"(h));
            asm("mul.rn.bf16x2 %0, %1, %2;" : "=r"(h) : "r"(u2[i]), "r"(0xbaabbaabu));
            asm("fma.rn.bf16x2 %0, %0, %1, %2;" : "+r"(u2[i]) : "r"(0x3f2b3f2bu), "r"(h));
            asm("fma.rn.bf16x2 %0, %1, %2, %3;" : "=r"(h) : "r"(a[i]), "r"(0x3e803e80u), "r"(cc[i]));
            asm("fma.rn.bf16x2 %0, %1, %2, %3;" : "=r"(u3[i]) : "r"(h), "r"(0x40004000u), "r"(b[i]));
        }
        if (PART & 1) stsm(dst + r * 512 + CP(3) * W_COMP, u3);
        if (PART & 2) stsm(dst + r * 512 + CP(2) * W_COMP, u2);
        if (PART & 4) stsm(dst + r * 512 + CP(1) * W_COMP, u1);
        if (PART & 8) {
            stsm(dst + r * 512 + CP(0) * W_COMP, a);
            stsm(dst + r * 512 + CP(4) * W_COMP, cc);
        }
    }
}

__device__ __forceinline__ int seq_row(int seg, int row_par, int n) {
    const int q = (seg & 1) ? seg * SEG - 1 + n : seg * SEG + SEG - n;
    return 2 * q + row_par;
}

#define WF2 0
struct XMaps { CUtensorMap m[2]; };
#define xmap xm.m[0]
__global__ void __cluster_dims__(2, 1, 1) __launch_bounds__(384, 1)
conv_kernel(const char* __restrict__ wp, const char* __restrict__ xp,
            const __grid_constant__ XMaps xm, const __grid_constant__ CUtensorMap omap) {
    extern __shared__ uint8_t smem_raw[];
    const uint32_t base = (smem_u32(smem_raw) + 1023u) & ~1023u;
    const uint32_t wbase = base + OFF_W;
    const uint32_t bar_base = base + OFF_BAR;
    const uint32_t wbar_b = bar_base + 256, wready_b = bar_base + 280;

    const int tid = threadIdx.x;
    const int warp = tid >> 5, lane = tid & 31;
    const int rank = blockIdx.x & 1;
    const int cluster = blockIdx.x >> 1;
    const int strip = cluster & 7, seg = cluster >> 3;
    const int fmode = rank ? FMODE1 : FMODE0;
#define WPN 26
#define XPN 0
#define XPR 1
#define XPW 0
    uint32_t c_start;
    {
        const uint32_t t = tid - 96, l = blockIdx.x * 10 + t;
        asm volatile("{\n\t.reg .pred p;\n\tsetp.lt.u32 p, %1, %2;\n\t@p prefetch.global.L2 [%0];\n\t}" ::"l"(wp + l * 128), "r"(t), "n"(WPN) : "memory");
        if (XPN) {
            const uint32_t t2 = tid - 128;
            asm volatile("{\n\t.reg .pred p;\n\tsetp.lt.u32 p, %1, %2;\n\t@p prefetch.global.L2 [%0];\n\t}"
                         ::"l"(xp + (uint32_t)(seq_row(seg, XPW, XPR) * (IMG_W * 192) + (strip * 64 + rank * 32) * 192 + t2 * 128)), "r"(t2), "n"(XPN) : "memory");
        }
    }
    asm volatile("mov.u32 %0, %clock;" : "=r"(c_start) :: "memory");

#define SX(j)
    const int uwarp = __shfl_sync(0xffffffffu, warp, 0);
    const bool el = elect();
#define WPM 0
#define NOF 0
#define PFPOS 0
#define PFBLK
#define NPF 0
#define PFT 400
#define PFS 0
#define PORD 0xc4ab9231
#define PFL 48
    if (NPF && (unsigned)(tid - 128) < NPF * PFL) {
        const int i = (tid - 128) / PFL, e = (PORD >> (i * 4)) & 15;
        const int prow = seq_row(seg, e >> 3, e & 7);
        const char* p = xp + (size_t)prow * (IMG_W * 192) + (strip * 64 + rank * 32) * 192 + (tid - 128 - i * PFL) * 128;
        if (PFT) while ((uint32_t)clock() - c_start < PFT + (warp - 4) * PFS) {}
        asm volatile("prefetch.global.L2 [%0];" ::"l"(p) : "memory");
        if (warp == 4) SX(7);
    }
    if (uwarp == 0 && el) {
        for (int i = 0; i < 3; ++i) mbar_init(wbar_b + i * 8, 1);
        if (!(NOF & 1)) asm volatile("fence.proxy.async.shared::cta;" ::: "memory");
        else asm volatile("fence.mbarrier_init.release.cluster;" ::: "memory");
        const int up = (seg & 1) ^ 1;
        SX(2);
#pragma unroll
        for (int j = 0; j < 3; ++j) {
#pragma unroll
            for (int i = 0; i < 3; ++i)
                asm volatile("cp.async.bulk.shared::cluster.global.mbarrier::complete_tx::bytes [%0], [%1], %2, [%3];"
                             ::"r"(wbase + ((up ? 2 - i : i) * 6 + j) * W_TAP), "l"(wp + (2 * (i * 3 + j) + rank) * W_TAP),
                               "r"(W_TAP), "r"(wbar_b + j * 8) : "memory");
        }
        SX(3);
        for (int j = 0; j < 3; ++j) mbar_expect_tx(wbar_b + j * 8, 3 * W_TAP);
        asm volatile("fence.mbarrier_init.release.cluster;" ::: "memory");
    }
    if (PFPOS == 1) { PFBLK }
#define RT 320
    if (uwarp == 2 && el) {
        for (int i = 0; i < 2; ++i) {
            mbar_init(bar_base + i * 128 + B_FULLA, 3);
            mbar_init(bar_base + i * 128 + B_FULLB, 2);
            mbar_init(bar_base + i * 128 + B_EMPTYE, 4);
            mbar_init(bar_base + i * 128 + B_EMPTYF, 4);
            mbar_init(bar_base + i * 128 + B_EMPTYB, 4);
            mbar_init(bar_base + i * 128 + B_HFULL, 1);
            mbar_init(bar_base + i * 128 + B_FFULL, 1);
            mbar_init(bar_base + i * 128 + B_SH, 4);
            mbar_init(bar_base + i * 128 + B_SF, 4);
            mbar_expect_tx(bar_base + i * 128 + B_HFULL, X_TX);
            mbar_expect_tx(bar_base + i * 128 + B_FFULL, 2 * X_TX);
            if (!WFA) mbar_arrive(bar_base + i * 128 + B_FULLA);
        }
        mbar_init(wready_b, 10);
        mbar_init(wready_b + 8, 4);
        mbar_init(wready_b + 16, WF2 ? 4 : 1);
        mbar_init(wready_b + 24, 4);
        mbar_init(wready_b + 32, 1);
        asm volatile("fence.mbarrier_init.release.cluster;" ::: "memory");
        asm volatile("fence.proxy.async.shared::cta;" ::: "memory");
    }
    if (uwarp == 10 && el) {
        asm volatile("prefetch.tensormap [%0];" ::"l"((uint64_t)(&xmap)) : "memory");
        asm volatile("prefetch.tensormap [%0];" ::"l"((uint64_t)(&xmap + 1)) : "memory");
        for (int i = 0; i < 4; ++i) mbar_init(bar_base + (i >> 1) * 128 + (i & 1) * B_FULLC, 1);
        for (int i = 0; i < 4; ++i) mbar_expect_tx(bar_base + (i >> 1) * 128 + (i & 1) * B_FULLC, (2 - (i & 1)) * IN_ROW);
        asm volatile("fence.mbarrier_init.release.cluster;" ::: "memory");
        if (!(NOF & 2)) asm volatile("fence.proxy.async.shared::cta;" ::: "memory");
    }
    __syncwarp();
    asm volatile("barrier.cluster.arrive.relaxed.aligned;" ::: "memory");
#define RSTEP 150
    if (uwarp == 10 && el) {
#pragma unroll
        for (int i = 0; i < 6; ++i) {
            const int wg = (RORD >> (i * 4 + 2)) & 1, n = (RORD >> (i * 4)) & 3;
            const uint32_t fb = bar_base + wg * 128 + (n == 2 ? B_FULLC : B_FULL0);
            if (i == 0 || RSTEP) while ((uint32_t)clock() - c_start < ROW_DELAY + i * RSTEP) {}
            const uint32_t dst = base + (n == 1 ? OFF_X + wg * X_BYTES : OFF_IN + wg * 4 * IN_ROW + n * 2 * IN_SLAB);
            load_row(dst, dst + (n == 1 ? 2 * IN_SLAB : IN_B - n * IN_SLAB), &xmap, fb, rank, strip, seq_row(seg, wg, n), true);
            if (i < 2) SX(4 + i);
            if (i == 5) SX(6);
        }
    }
    __syncwarp();
#define ST(j)
    ST(0);
    asm volatile("barrier.cluster.wait.aligned;" ::: "memory");
#define RLW 1
#define WX 4
#define HW0 11
#define HW1 9
#define P1M 1
#define P2M 6
#define WF1 0
    if (uwarp < 4 || uwarp == HW0 || uwarp == HW1) {
        uint32_t ga[36];
        const int uw = uwarp < 4 ? uwarp : uwarp == HW0 ? 4 : 5;
        const uint32_t unit = wbase + uw * W_K8;
        ST(1);
        mbar_wait(wbar_b, 0);
        ST(2);
        wt_load(ga, unit, lane);
        __syncwarp();
        wt_store<15>(ga, unit, lane);
        ST(5);
        if (WF1) asm volatile("fence.proxy.async.shared::cta;" ::: "memory");
        mbar_arrive_warp(wready_b);
        ST(6);
    } else if (uwarp < 8) {
        uint32_t ga[36], gb[36], gc[36];
        const uint32_t unit = wbase + (uwarp + 2) * W_K8;
        ST(1);
        mbar_wait(wbar_b + 8, 0);
        wt_load(ga, unit, lane);
        mbar_wait(wbar_b + (uwarp < 6 ? 8 : 16), 0);
        wt_load(gb, unit + 4 * W_K8, lane);
        mbar_wait(wbar_b + 16, 0);
        ST(2);
        wt_load(gc, unit + 8 * W_K8, lane);
        __syncwarp();
        wt_store<P1M>(ga, unit, lane);
        wt_store<P1M>(gb, unit + 4 * W_K8, lane);
        wt_store<P1M>(gc, unit + 8 * W_K8, lane);
        if (WF1) asm volatile("fence.proxy.async.shared::cta;" ::: "memory");
        mbar_arrive_warp(wready_b);
        ST(3);
        if (P2M) {
            wt_store<P2M>(ga, unit, lane);
            wt_store<P2M>(gb, unit + 4 * W_K8, lane);
            wt_store<P2M>(gc, unit + 8 * W_K8, lane);
            mbar_arrive_warp(wready_b + 24);
        }
        ST(4);
        wt_store<15 - P1M - P2M>(ga, unit, lane);
        wt_store<15 - P1M - P2M>(gb, unit + 4 * W_K8, lane);
        wt_store<15 - P1M - P2M>(gc, unit + 8 * W_K8, lane);
        ST(5);
        if (WF2) asm volatile("fence.proxy.async.shared::cta;" ::: "memory");
        mbar_arrive_warp(wready_b + (WF2 ? 16 : 8));
        ST(6);
    }

    if (uwarp >= 8) {
        asm volatile("setmaxnreg.dec.sync.aligned.u32 24;");
        {
            const int wg = uwarp & 1;
            const uint32_t bar = bar_base + wg * 128;
            const int step = (seg & 1) ? 2 : -2;
            if (uwarp < 10) {
                const uint32_t in = base + OFF_IN + wg * 4 * IN_ROW;
                const char* pf = xp + (strip * 64 + rank * 32) * 192;
                int row = seq_row(seg, wg, 0);
#pragma unroll 1
                for (int t = 0; t < NIT; ++t, row += 3 * step) {
#pragma unroll
                    for (int g = 0; g < 3; ++g) {
                        const int sl = g == 2 ? 2 : (g ^ rank ^ 1);
                        const uint32_t fb = bar + (g == 2 ? B_FULLB : B_FULLA);
                        mbar_wait_h(bar + B_EMPTYE + g * 8, t & 1);
                        STAMP(t, 6 + g);
                        if (el) {
                            const bool ld = t < NIT - 1 || sl == 0;
                            if (ld) {
                                if (g == 2) load_row(in + 2 * SL3, in + IN_B + SL3, &xmap, fb, rank, strip, row + 6 * step, true);
                                load_row(in + sl * 2 * IN_SLAB, in + IN_B + sl * IN_SLAB, &xmap, fb, rank, strip, row + (g == 2 ? 5 : 4 * sl) * step, true);
                            }
                            mbar_expect_tx(fb, ld ? (g == 2 ? 2 * IN_ROW : IN_ROW) : 0);
                            if (g == 2 && t == 0) mbar_arrive_remote(mapa(fb, rank ^ 1));
                            const int n = 3 * t + g + 1, prow = row + (g + 1 + PF) * step;
                            if (n >= PF0 && n + PF < SEG + 2 && (unsigned)prow < IMG_H)
                                asm volatile("cp.async.bulk.prefetch.L2.global [%0], %1;"
                                             ::"l"(pf + (size_t)prow * (IMG_W * 192)), "r"(32 * 192) : "memory");
#define EPT 0
                            if (EPT && n < 5) {
                                const int e0 = (EPT >> (n * 8 - 8)) & 15, e1 = (EPT >> (n * 8 - 4)) & 15;
                                if (e0) asm volatile("cp.async.bulk.prefetch.L2.global [%0], %1;"
                                                     ::"l"(pf + (size_t)(row + (e0 - 3 * t) * step) * (IMG_W * 192)), "r"(32 * 192) : "memory");
                                if (e1) asm volatile("cp.async.bulk.prefetch.L2.global [%0], %1;"
                                                     ::"l"(pf + (size_t)(row + (e1 - 3 * t) * step) * (IMG_W * 192)), "r"(32 * 192) : "memory");
                            }
                        }
                        __syncwarp();
                        if (g) STAMP(t, 8 + g);
                    }
                }
            } else {
                const uint32_t src = base + OFF_X + wg * X_BYTES;
                const uint32_t r_bar = mapa(bar, rank ^ 1);
                if (wg == 0 && lane < 4)
                    asm volatile("mbarrier.arrive.shared::cta.b64 _, [%0], 4;" ::"r"(bar + (lane >> 1) * 128 + B_EMPTYE + (lane & 1) * 8) : "memory");
                __syncwarp();
                if (wg == RLW) {
                    if (P2M) {
                        mbar_wait(wready_b + 24, 0);
                        asm volatile("fence.proxy.async.shared::cta;" ::: "memory");
                        mbar_arrive_warp(wready_b + 32);
                    }
                    if (!WF2) {
                        mbar_wait(wready_b + 8, 0);
                        asm volatile("fence.proxy.async.shared::cta;" ::: "memory");
                        if (WFA) { if (lane < 2) mbar_arrive(bar_base + lane * 128 + B_FULLA); }
                        else mbar_arrive_warp(wready_b + 16);
                    }
                    if (RLW) ST(7);
                }
                int row = seq_row(seg, wg, 1);
#pragma unroll 1
                for (int t = 0; t < NIT; ++t, row += 3 * step) {
                    const bool last = t == NIT - 1;
                    mbar_wait_h(bar + B_SH, t & 1);
                    STAMP(t, 0);
                    if (el) {
                        asm volatile("fence.proxy.async.shared::cta;" ::: "memory");
                        tma_store_4d(&omap, src + 2 * X_UNIT, 0, strip * 16, rank, row + step, EF(t, 2));
                        asm volatile("cp.async.bulk.commit_group;" ::: "memory");
                        if (!last) {
                            mbar_expect_tx(bar + B_HFULL, X_TX);
                            asm volatile("cp.async.bulk.wait_group.read 0;" ::: "memory");
                            mbar_arrive_remote(r_bar + B_FULLA);
                        }
                    }
                    __syncwarp();
                    STAMP(t, 1);
                    mbar_wait_h(bar + B_SF, t & 1);
                    STAMP(t, 2);
                    if (el) {
                        asm volatile("fence.proxy.async.shared::cta;" ::: "memory");
                        const int orow = row + (last ? 0 : 2 * rank * step);
                        tma_store_4d(&omap, src, 0, strip * 16, last ? rank : 0, orow, EF(t, 0));
                        if (!last) tma_store_4d(&omap, src + X_UNIT, 0, strip * 16, 1, orow, EF(t, 1));
                        asm volatile("cp.async.bulk.commit_group;" ::: "memory");
                        if (!last) mbar_expect_tx(bar + B_FFULL, t == NIT - 2 ? X_TX : 2 * X_TX);
                        asm volatile("cp.async.bulk.wait_group.read 0;" ::: "memory");
                        if (!last) mbar_arrive_remote(r_bar + B_FULLB);
                    }
                    __syncwarp();
                    STAMP(t, 3);
                }
            }
        }
    } else {
        const int wg = uwarp >> 2;
        const int w4 = warp & 3;
        if (RT >= 256) asm volatile("setmaxnreg.inc.sync.aligned.u32 240;");
        ST(7);
        Ctx c;
        c.bar = bar_base + wg * 128;
        c.wdesc = ((wbase & 0x3FFFF) >> 4) | ((uint32_t)(512 >> 4) << 16);
        c.wready = wready_b;
        c.wg = wg;
        c.k = ~0u;
        c.zero = 0;
        c.tlo2 = bar_base + 576 - bar_base * 4;
        c.tlo = 320;
        {
            const int m = lane >> 3, gg = lane & 7, hl = m >> 1;
            const int rho0 = (m & 1) ? (8 * w4 + gg + 2) : (36 + 8 * w4 + gg);
            const int rho1 = rho0 + 2;
            const uint32_t in = base + OFF_IN + wg * 4 * IN_ROW;
            c.ld0 = in + IN_B + rho0 * 32 + ((hl ^ ((rho0 >> 2) & 1)) << 4);
            c.ld1 = in + IN_B + rho1 * 32 + ((hl ^ ((rho1 >> 2) & 1)) << 4);
            c.vz = (rho0 & 2) << 3;
            c.ua = in - 2 * (in + IN_B);
        }
        c.xbuf = base + OFF_X + wg * X_BYTES + (tid & 127) * 16;
        c.r_off = mapa(c.bar, rank ^ 1) - c.bar;
        c.ld0 = __shfl_sync(0xffffffffu, c.ld0, lane);
        c.ld1 = __shfl_sync(0xffffffffu, c.ld1, lane);
        c.xbuf = __shfl_sync(0xffffffffu, c.xbuf, lane);
        TL(1);
        TLC(20);
        if (rank == 0) consumer<0>(c);
        else consumer<1>(c);
        TLC(21);
    }
}

typedef CUresult (*EncodeFn)(CUtensorMap*, CUtensorMapDataType, cuuint32_t, void*, const cuuint64_t*,
                             const cuuint64_t*, const cuuint32_t*, const cuuint32_t*, CUtensorMapInterleave,
                             CUtensorMapSwizzle, CUtensorMapL2promotion, CUtensorMapFloatOOBfill);

}

extern "C" void kernel_launch(void* const* d_in, const int* in_sizes, int n_in, void* d_out, int out_size) {
    (void)in_sizes; (void)n_in; (void)out_size;
    static EncodeFn encode = nullptr;
    if (!encode) {
        void* fn = nullptr;
        cudaDriverEntryPointQueryResult qres;
        cudaGetDriverEntryPoint("cuTensorMapEncodeTiled", &fn, cudaEnableDefault, &qres);
        encode = (EncodeFn)fn;
        cudaFuncSetAttribute(conv_kernel, cudaFuncAttributeMaxDynamicSharedMemorySize, SMEM_BYTES);
    }
    XMaps xm;
    CUtensorMap omap;
    cuuint32_t estr5[5] = {1, 1, 1, 1, 1};
    {
        cuuint64_t dims[5] = {(cuuint64_t)CH, 2, (cuuint64_t)IMG_W / 4, 2, (cuuint64_t)IMG_H};
        cuuint64_t strides[4] = {(cuuint64_t)CH * 2, (cuuint64_t)CH * 2 * 4, (cuuint64_t)CH * 2 * 2,
                                 (cuuint64_t)IMG_W * CH * 2};
        cuuint32_t box[5] = {16, 2, 18, 2, 1};
        encode(&xmap, CU_TENSOR_MAP_DATA_TYPE_BFLOAT16, 5, d_in[0], dims, strides, box, estr5,
               CU_TENSOR_MAP_INTERLEAVE_NONE, CU_TENSOR_MAP_SWIZZLE_32B, PROMO,
               CU_TENSOR_MAP_FLOAT_OOB_FILL_NONE);
        box[0] = 32;
        encode(&xm.m[1], CU_TENSOR_MAP_DATA_TYPE_BFLOAT16, 5, d_in[0], dims, strides, box, estr5,
               CU_TENSOR_MAP_INTERLEAVE_NONE, CU_TENSOR_MAP_SWIZZLE_64B, PROMO,
               CU_TENSOR_MAP_FLOAT_OOB_FILL_NONE);
    }
    {
        cuuint64_t dims[5] = {32, 2, (cuuint64_t)IMG_H * IMG_W / 4, 3, 2};
        cuuint64_t strides[4] = {(cuuint64_t)CH * 2, (cuuint64_t)CH * 2 * 4, 64, (cuuint64_t)CH * 2 * 2};
        cuuint32_t box[5] = {32, 2, 16, 3, 1};
        encode(&omap, CU_TENSOR_MAP_DATA_TYPE_BFLOAT16, 5, d_out, dims, strides, box, estr5,
               CU_TENSOR_MAP_INTERLEAVE_NONE, CU_TENSOR_MAP_SWIZZLE_NONE, CU_TENSOR_MAP_L2_PROMOTION_NONE,
               CU_TENSOR_MAP_FLOAT_OOB_FILL_NONE);
    }
    conv_kernel<<<NUM_CTAS, 384, SMEM_BYTES>>>((const char*)d_in[1], (const char*)d_in[0], xm, omap);
}
```

```cpp
#include <cuda_runtime.h>
#include <cuda_bf16.h>
#include <cuda.h>
#include <stdint.h>

namespace {

#define PFIRST
#define GAPB 2
#define PKH0 3
#define PKH1 PKH0
#define PKH (RANK == 0 ? PKH0 : PKH1)
#define KPS0 2
#define KPS1 KPS0
#define KPS (RANK == 0 ? KPS0 : KPS1)
#define EPK0 11
#define EPK1 EPK0
#define EPK (RANK == 0 ? EPK0 : EPK1)
#define SPK0 15
#define SPK1 SPK0
#define SPK (RANK == 0 ? SPK0 : SPK1)
#define KPE 0
#define HKS 3
#define ST_EF
#define PF 6
#define PF0 5
#define EQ0 0x7fa
#define EQ1 0x7fe
#define PLA0 0xf0223445566ff045ull
#define PLA1 0xff012445566ff045ull
#define PLB0 0x4444459aab000000ull
#define PLB1 0x4444459aab000000ull
#define FMODE0 1
#define FMODE1 1
#define ORD 0
#define FMODE (RANK == 0 ? FMODE0 : FMODE1)
#define LT0 0
#define LT1 0
#define LATE(n) (((RANK == 0 ? LT0 : LT1) >> (n)) & 1)
#define LL0 0x10
#define LL1 0x10
#define LLATE(n) (((RANK == 0 ? LL0 : LL1) >> (n)) & 1)
#define PO0 0x012654
#define PO1 PO0
#define PG(g) (((RANK == 0 ? PO0 : PO1) >> (20 - (g) * 4)) & 7)
#define M1FIRST (PG(2) >= 4 ? PG(2) & 3 : PG(3) & 3)
#define EBSLOT (PG(2) == 2 ? 8 : PG(3) == 2 ? 9 : 10)
#define NW0 0
#define NW1 NW0
#define NW(n) (((RANK == 0 ? NW0 : NW1) >> (n)) & 1)
#define DEC 1
#define RORD 0x675231
#define PW0 0
#define PW1 1
#define EPO 0x8c04ab9231ull
#define PROMO CU_TENSOR_MAP_L2_PROMOTION_L2_128B
#define ZEND 1
#define HPIN 0
#define LL2 0x20
#define LLATE2(n) ((LL2 >> (n)) & 1)
#define CPT 0x01234
#define CP(k) ((CPT >> (16 - 4 * (k))) & 7)
#define MEF 0
#define DEFW 0
#define PKSLOT 7
#define EQ(n) (((RANK == 0 ? EQ0 : EQ1) >> (n)) & 1)
#define LAG0 6
#define LEAD0 9
#define LAG1 LAG0
#define LEAD1 LEAD0
#define LAGPOS (RANK == 0 ? LAG0 : LAG1)
#define LEADPOS (RANK == 0 ? LEAD0 : LEAD1)
#define LAGK (LEADPOS > 20 ? 1 : LEADPOS >= 12 || LEADPOS < LAGPOS ? 2 : 1)
#define SEND1 4
#define SEND2 6
#define TL(slot)
#define TLC(slot)
constexpr int IMG_H = 512, IMG_W = 512, CH = 96;
constexpr int IN_SLAB = 72 * 32;
constexpr int IN_ROW = 3 * IN_SLAB;
constexpr int SL0 = 0, SL4 = IN_SLAB, SL2 = 2 * IN_SLAB, SL3 = 3 * IN_SLAB, IN_B = 8 * IN_SLAB;
constexpr int W_K8 = 3 * 512;
constexpr int W_TAP = 6 * W_K8;
constexpr int W_COMP = 3 * W_TAP;
constexpr int W_BYTES = 5 * W_COMP;
constexpr int X_CH = 32 * 64;
constexpr int X_UNIT = 3 * X_CH;
constexpr int X_BYTES = 3 * X_UNIT;
constexpr int X_TX = X_UNIT;
constexpr int SEG = 32;
constexpr int NIT = 11;
constexpr int NUM_CTAS = 128;
#define LAY 3
constexpr int OFF_W = LAY == 0 ? 0 : LAY == 1 ? 2 * X_BYTES : LAY == 2 ? 2 * X_BYTES + 8 * IN_ROW : 8 * IN_ROW;
constexpr int OFF_X = LAY == 0 ? W_BYTES : LAY == 3 ? W_BYTES + 8 * IN_ROW : 0;
constexpr int OFF_IN = LAY == 3 ? 0 : LAY == 2 ? 2 * X_BYTES : W_BYTES + 2 * X_BYTES;
constexpr int OFF_BAR = W_BYTES + 2 * X_BYTES + 8 * IN_ROW;
constexpr int SMEM_BYTES = 1024 + OFF_BAR + 1024;
static_assert(SMEM_BYTES <= 232448, "smem");
#define RDEL 400
constexpr uint32_t ROW_DELAY = RDEL;
constexpr int B_FULL0 = 0, B_FULLA = 8, B_FULLB = 16, B_FULLC = 24, B_EMPTYE = 32, B_EMPTYF = 40, B_EMPTYB = 48, B_HFULL = 56,
              B_FFULL = 64, B_SH = 72, B_SF = 80;

__device__ __forceinline__ uint32_t smem_u32(const void* p) {
    return (uint32_t)__cvta_generic_to_shared(p);
}
__device__ __forceinline__ void mbar_init(uint32_t bar, uint32_t count) {
    asm volatile("mbarrier.init.shared::cta.b64 [%0], %1;" ::"r"(bar), "r"(count) : "memory");
}
__device__ __forceinline__ void mbar_expect_tx(uint32_t bar, uint32_t bytes) {
    asm volatile("mbarrier.arrive.expect_tx.shared::cta.b64 _, [%0], %1;" ::"r"(bar), "r"(bytes) : "memory");
}
__device__ __forceinline__ void mbar_arrive(uint32_t bar) {
    asm volatile("mbarrier.arrive.shared::cta.b64 _, [%0];" ::"r"(bar) : "memory");
}
__device__ __forceinline__ void mbar_arrive_warp(uint32_t bar) {
    __syncwarp();
    asm volatile("{\n\t.reg .pred p;\n\telect.sync _|p, 0xffffffff;\n\t@p mbarrier.arrive.shared::cta.b64 _, [%0];\n\t}" ::"r"(bar) : "memory");
}
__device__ __forceinline__ void mbar_arrive_remote(uint32_t rbar) {
    asm volatile("mbarrier.arrive.relaxed.cluster.shared::cluster.b64 _, [%0];" ::"r"(rbar) : "memory");
}
__device__ __forceinline__ void mbar_expect_tx_remote(uint32_t rbar, uint32_t bytes) {
    asm volatile("mbarrier.arrive.expect_tx.relaxed.cluster.shared::cluster.b64 _, [%0], %1;" ::"r"(rbar), "r"(bytes) : "memory");
}
__device__ __forceinline__ void mbar_wait(uint32_t bar, uint32_t parity) {
    uint32_t done;
    for (;;) {
        asm volatile(
            "{\n\t.reg .pred p;\n\t"
            "mbarrier.try_wait.parity.shared::cta.b64 p, [%1], %2;\n\t"
            "selp.u32 %0, 1, 0, p;\n\t}"
            : "=r"(done) : "r"(bar), "r"(parity) : "memory");
        if (done) return;
    }
}
#define STAMP(t, j)
__device__ __forceinline__ uint32_t mbar_try(uint32_t bar, uint32_t parity) {
    uint32_t done;
    asm volatile("{\n\t.reg .pred p;\n\tmbarrier.try_wait.parity.shared::cta.b64 p, [%1], %2;\n\tselp.u32 %0, 1, 0, p;\n\t}"
                 : "=r"(done) : "r"(bar), "r"(parity) : "memory");
    return done;
}
#define HSL 0
__device__ __forceinline__ void mbar_wait_h(uint32_t bar, uint32_t parity) {
    mbar_wait(bar, parity);
}
__device__ __forceinline__ bool elect() {
    uint32_t el;
    asm volatile("{\n\t.reg .pred p;\n\telect.sync _|p, 0xffffffff;\n\tselp.u32 %0, 1, 0, p;\n\t}" : "=r"(el));
    return el;
}
__device__ __forceinline__ uint32_t mapa(uint32_t addr, uint32_t rank) {
    uint32_t r;
    asm("mapa.shared::cluster.u32 %0, %1, %2;" : "=r"(r) : "r"(addr), "r"(rank));
    return r;
}
__device__ __forceinline__ void tma_load_5d(uint32_t dst, const CUtensorMap* map, uint32_t bar,
                                            int c0, int c1, int c2, int c3, int c4, bool keep) {
    asm volatile(
        "cp.async.bulk.tensor.5d.shared::cluster.global.mbarrier::complete_tx::bytes "
        "[%0], [%1, {%3, %4, %5, %6, %7}], [%2];"
        ::"r"(dst), "l"((uint64_t)map), "r"(bar), "r"(c0), "r"(c1), "r"(c2), "r"(c3), "r"(c4) : "memory");
}
#define MRG 1
#define EFN 99
#define EFM 7
#define EFM2 0
#define EF(t, u) ((((t) < EFN ? EFM : EFM2) >> (u)) & 1)
__device__ __forceinline__ void tma_store_4d(const CUtensorMap* map, uint32_t src, int c0, int c1, int c2, int c3, bool ef) {
    uint64_t pol, pn;
    asm volatile("createpolicy.fractional.L2::evict_first.b64 %0, 1.0;" : "=l"(pol));
    asm volatile("createpolicy.fractional.L2::evict_normal.b64 %0, 1.0;" : "=l"(pn));
    if (!ef) pol = pn;
    asm volatile("cp.async.bulk.tensor.5d.global.shared::cta.bulk_group.L2::cache_hint [%0, {%2, %2, %3, %2, %4}], [%1], %5;"
                 ::"l"((uint64_t)map), "r"(src), "r"(c0), "r"(c3 * 128 + c1), "r"(c2), "l"(pol) : "memory");
}
__device__ __forceinline__ void load_row(uint32_t dst, uint32_t dstb, const CUtensorMap* xmap, uint32_t fb, int rank, int strip, int row, bool keep) {
    tma_load_5d(dst, xmap + 1, fb, rank * 64, 0, strip * 16 - 1, 0, row, keep);
    tma_load_5d(dstb, xmap, fb, 32 + rank * 16, 0, strip * 16 - 1, 0, row, keep);
}

__device__ __forceinline__ void wgmma_fence() { asm volatile("wgmma.fence.sync.aligned;" ::: "memory"); }
__device__ __forceinline__ void wgmma_commit() { asm volatile("wgmma.commit_group.sync.aligned;" ::: "memory"); }
template <int N>
__device__ __forceinline__ void wgmma_wait() { asm volatile("wgmma.wait_group.sync.aligned %0;" ::"n"(N) : "memory"); }

template <int SA>
__device__ __forceinline__ void wgmma_m64n96k16(float (&d)[48], const uint32_t* a, uint64_t db, int scale_d) {
    asm volatile(
        "{\n\t.reg .pred p;\n\t"
        "setp.ne.b32 p, %53, 0;\n\t"
        "wgmma.mma_async.sync.aligned.m64n96k16.f32.bf16.bf16 "
        "{%0, %1, %2, %3, %4, %5, %6, %7, %8, %9, %10, %11, %12, %13, %14, %15, "
        " %16, %17, %18, %19, %20, %21, %22, %23, %24, %25, %26, %27, %28, %29, %30, %31, "
        " %32, %33, %34, %35, %36, %37, %38, %39, %40, %41, %42, %43, %44, %45, %46, %47}, "
        "{%48, %49, %50, %51}, %52, p, %54, 1, 1;\n\t}"
        : "+f"(d[0]), "+f"(d[1]), "+f"(d[2]), "+f"(d[3]), "+f"(d[4]), "+f"(d[5]), "+f"(d[6]), "+f"(d[7]),
          "+f"(d[8]), "+f"(d[9]), "+f"(d[10]), "+f"(d[11]), "+f"(d[12]), "+f"(d[13]), "+f"(d[14]), "+f"(d[15]),
          "+f"(d[16]), "+f"(d[17]), "+f"(d[18]), "+f"(d[19]), "+f"(d[20]), "+f"(d[21]), "+f"(d[22]), "+f"(d[23]),
          "+f"(d[24]), "+f"(d[25]), "+f"(d[26]), "+f"(d[27]), "+f"(d[28]), "+f"(d[29]), "+f"(d[30]), "+f"(d[31]),
          "+f"(d[32]), "+f"(d[33]), "+f"(d[34]), "+f"(d[35]), "+f"(d[36]), "+f"(d[37]), "+f"(d[38]), "+f"(d[39]),
          "+f"(d[40]), "+f"(d[41]), "+f"(d[42]), "+f"(d[43]), "+f"(d[44]), "+f"(d[45]), "+f"(d[46]), "+f"(d[47])
        : "r"(a[0]), "r"(a[1]), "r"(a[2]), "r"(a[3]), "l"(db), "r"(scale_d), "n"(SA));
}

template <int N>
__device__ __forceinline__ void fence_regs(float (&r)[N]) {
#pragma unroll
    for (int i = 0; i < N; ++i) asm volatile("" : "+f"(r[i])::"memory");
}

__device__ __forceinline__ uint32_t bf2_add(uint32_t a, uint32_t b) {
    uint32_t r;
    asm volatile("add.rn.bf16x2 %0, %1, %2;" : "=r"(r) : "r"(a), "r"(b));
    return r;
}
__device__ __forceinline__ uint32_t bf2_sub(uint32_t a, uint32_t b) {
    uint32_t r;
    asm volatile("sub.rn.bf16x2 %0, %1, %2;" : "=r"(r) : "r"(a), "r"(b));
    return r;
}
template <uint32_t B>
__device__ __forceinline__ uint32_t bf2_fma(uint32_t a, uint32_t cc) {
    uint32_t r;
    asm volatile("fma.rn.bf16x2 %0, %1, %2, %3;" : "=r"(r) : "r"(a), "r"(B), "r"(cc));
    return r;
}
__device__ __forceinline__ uint32_t pack_bf16(float a, float b) {
    __nv_bfloat162 v = __floats2bfloat162_rn(a, b);
    return *reinterpret_cast<uint32_t*>(&v);
}

__device__ __forceinline__ uint32_t opaque_add(uint32_t a, uint32_t b) {
    uint32_t r;
    asm volatile("add.u32 %0, %1, %2;" : "=r"(r) : "r"(a), "r"(b));
    return r;
}
template <int K>
__device__ __forceinline__ void make_quads(uint32_t (&q)[12], const uint32_t (&x)[24], const uint32_t (&d2)[24],
                                           const uint32_t (&u)[24], int kc, uint32_t coef = 0) {
    uint32_t e[8];
#pragma unroll
    for (int i = 0; i < 8; ++i) e[i] = K == 1 ? bf2_add(x[kc * 8 + i], d2[kc * 8 + i]) : bf2_sub(x[kc * 8 + i], d2[kc * 8 + i]);
#pragma unroll
    for (int jj = 0; jj < 3; ++jj) {
        const int j = jj == 0 ? 1 : jj == 1 ? 0 : 2;
#pragma unroll
        for (int hl = 0; hl < 2; ++hl) {
#pragma unroll
            for (int h = 0; h < 2; ++h) {
                const int i = ((j + h) >> 1) * 4 + hl * 2 + ((j + h) & 1);
                const uint32_t uu = u[kc * 8 + i];
                if (K < 0) asm volatile("fma.rn.bf16x2 %0, %1, %2, %3;" : "=r"(q[j * 4 + hl * 2 + h]) : "r"(uu), "r"(coef), "r"(e[i]));
                else q[j * 4 + hl * 2 + h] = K == 0 ? bf2_fma<0x3f003f00u>(uu, e[i]) : K == 1 ? bf2_sub(e[i], uu)
                                      : K == 2 ? bf2_fma<0x40404040u>(e[i], uu) : bf2_fma<0xc000c000u>(uu, e[i]);
            }
        }
    }
}
template <bool MAKE_U, bool TIE>
__device__ __forceinline__ void make_mid(uint32_t (&q)[12], uint32_t (&d1)[24], const uint32_t (&d2)[24], uint32_t (&u)[24], int kc,
                                         const uint32_t (&d3)[24], uint32_t wg) {
    uint32_t y[8];
#pragma unroll
    for (int i = 0; i < 8; ++i) {
        y[i] = bf2_sub(d2[kc * 8 + i], d3[kc * 8 + i]);
        if (MAKE_U) asm volatile("sub.rn.bf16x2 %0, %0, %1;" : "+r"(u[kc * 8 + i]) : "r"(d1[kc * 8 + i]));
        if (TIE) asm volatile("{\n\t.reg .pred q;\n\tsetp.ne.u32 q, %3, 7;\n\t@q fma.rn.bf16x2 %0, %0, %2, %1;\n\t}" : "+r"(d1[kc * 8 + i]) : "r"(y[i]), "r"(0x40004000u), "r"(wg));
        else asm volatile("fma.rn.bf16x2 %0, %0, %2, %1;" : "+r"(d1[kc * 8 + i]) : "r"(y[i]), "r"(0x40004000u));
    }
#pragma unroll
    for (int jj = 0; jj < 3; ++jj) {
        const int j = jj == 0 ? 1 : jj == 1 ? 0 : 2;
#pragma unroll
        for (int hl = 0; hl < 2; ++hl) {
#pragma unroll
            for (int h = 0; h < 2; ++h) {
                const int i = ((j + h) >> 1) * 4 + hl * 2 + ((j + h) & 1);
                q[j * 4 + hl * 2 + h] = bf2_fma<0x3fc03fc0u>(y[i], u[kc * 8 + i]);
            }
        }
    }
}

struct Ctx {
    uint32_t bar;
    uint32_t wdesc;
    uint32_t wready, wg, tlo, k, zero, tlo2, vz, ua;
    int rk;
    uint32_t ld0, ld1;
    uint32_t xbuf;
    uint32_t r_off;
};

__device__ __forceinline__ void sb(const Ctx& c) {
    asm volatile("{\n\t.reg .pred q;\n\tsetp.eq.u32 q, %1, 7;\n\t@q mov.u32 %0, %clock;\n\t}" : "+r"(const_cast<Ctx&>(c).vz) : "r"(c.wg) : "memory");
}
__device__ __forceinline__ void sbz(const Ctx& c) {
    asm volatile("{\n\t.reg .pred q;\n\tsetp.eq.u32 q, %1, 7;\n\t@q mov.u32 %0, %clock;\n\t}" : "+r"(const_cast<Ctx&>(c).zero) : "r"(c.wg) : "memory");
}
#define FTW(n)
#define FTM
__device__ __forceinline__ void sbk(Ctx& c) {
    asm volatile("{\n\t.reg .pred q;\n\tsetp.eq.u32 q, %1, 7;\n\t@q mov.u32 %0, %clock;\n\t}" : "+r"(c.k) : "r"(c.wg) : "memory");
}
template <int OFF>
__device__ __forceinline__ void ldsm(uint32_t* r, uint32_t a, uint32_t ua) {
    asm volatile("{\n\t.reg .u32 t;\n\tadd.u32 t, %4, %5;\n\tldmatrix.sync.aligned.m8n8.x4.shared.b16 {%0, %1, %2, %3}, [t + %6];\n\t}"
                 : "=r"(r[0]), "=r"(r[1]), "=r"(r[2]), "=r"(r[3]) : "r"(a), "r"(ua), "n"(OFF) : "memory");
}
template <bool PLUS>
__device__ __forceinline__ uint32_t addr2(uint32_t b, uint32_t t) {
    uint32_t r;
    if (PLUS) asm volatile("mad.lo.s32 %0, %1, 2, %2;" : "=r"(r) : "r"(b), "r"(t));
    else asm volatile("{\n\t.reg .s32 x;\n\tneg.s32 x, %2;\n\tmad.lo.s32 %0, %1, 2, x;\n\t}" : "=r"(r) : "r"(b), "r"(t));
    return r;
}
template <int SLOT, int KC>
__device__ __forceinline__ void ld_chunk_t(uint32_t (&r)[24], const Ctx& c, uint32_t ua, uint32_t ub) {
    if (KC == 2) {
        ldsm<SLOT>(&r[16], c.ld0, ub);
        ldsm<SLOT>(&r[20], c.ld1, ub);
    } else {
        ldsm<2 * SLOT + KC * 16>(&r[KC * 8], addr2<KC == 0>(c.ld0, c.vz), ua);
        ldsm<2 * SLOT + 16 - KC * 16>(&r[KC * 8 + 4], addr2<KC != 0>(c.ld1, c.vz), ua);
    }
}
#define ld_chunk(r, c, slot, kc) ld_chunk_t<slot, kc>(r, c, c.ua, 0)

__device__ __forceinline__ void mma3p(float (&acc)[48], const uint32_t* q0, const uint32_t* q1, const uint32_t* q2,
                                      const Ctx& c, int k, int kc, bool fresh) {
    uint32_t wd;
    asm volatile("mov.b32 %0, %1;" : "=r"(wd) : "r"(c.wdesc));
    wgmma_fence();
#pragma unroll
    for (int j = 0; j < 3; ++j) {
        const uint32_t lo = wd + (uint32_t)((CP(k) * W_COMP + j * W_TAP + (kc == 2 ? 4 - 4 * c.rk : kc + 2 * c.rk) * W_K8) >> 4);
        const uint32_t hi = (uint32_t)((kc == 2 ? W_K8 : 2 * W_K8) >> 4) | (2u << 30);
        uint64_t db;
        asm("mov.b64 %0, {%1, %2};" : "=l"(db) : "r"(lo), "r"(hi));
        if (k == 3 && c.rk == 1) wgmma_m64n96k16<-1>(acc, j == 0 ? q0 : j == 1 ? q1 : q2, db, (fresh && j == 0) ? 0 : 1);
        else wgmma_m64n96k16<1>(acc, j == 0 ? q0 : j == 1 ? q1 : q2, db, (fresh && j == 0) ? 0 : 1);
    }
    wgmma_commit();
}
__device__ __forceinline__ void mma3(float (&acc)[48], const uint32_t (&q)[12], const Ctx& c, int k, int kc, bool fresh) {
    mma3p(acc, &q[0], &q[4], &q[8], c, k, kc, fresh);
}
__device__ __forceinline__ void make_dup(uint32_t (&q)[12], const uint32_t (&u)[24], const Ctx& c, int kc) {
#pragma unroll
    for (int i = 0; i < 4; ++i)
        q[kc * 4 + i] = opaque_add(u[kc * 8 + (i & 1) * 3 + (i >> 1) * 2 + 1], c.zero);
}
__device__ __forceinline__ void mma3d(float (&acc)[48], const uint32_t (&u)[24], const uint32_t (&q)[12], const Ctx& c, int k, int kc, int first = 0) {
    mma3p(acc, &u[kc * 8], &q[kc * 4], &u[kc * 8 + 4], c, k, kc, kc == first);
}
__device__ __forceinline__ void mma3u(float (&acc)[48], const uint32_t (&u)[24], uint32_t (&q)[12], const Ctx& c, int kc) {
    make_dup(q, u, c, kc);
    mma3d(acc, u, q, c, 3, kc);
}

__device__ __forceinline__ uint32_t pack_word(const float (&acc)[48], int i, int m) {
    const int o = ((i % 3) * 4 + m) * 4 + (i / 3) * 2;
    return pack_bf16(acc[o], acc[o + 1]);
}
__device__ __forceinline__ void st_async(uint32_t addr, uint32_t r0, uint32_t r1, uint32_t r2, uint32_t r3, uint32_t rbar) {
    asm volatile("st.async.weak.shared::cluster.mbarrier::complete_tx::bytes.v4.b32 [%0], {%1, %2, %3, %4}, [%5];"
                 ::"r"(addr), "r"(r0), "r"(r1), "r"(r2), "r"(r3), "r"(rbar) : "memory");
}
template <int I>
__device__ __forceinline__ void send_acc(float (&acc)[48], uint32_t (&kp)[24], const Ctx& c, int n, int at, int spk) {
    if (n == (at < spk ? at : spk)) {
        fence_regs(acc);
#pragma unroll
        for (int m = 0; m < 4; ++m) {
            if (at > spk) asm volatile("add.rn.bf16x2 %0, %0, %1;" : "+r"(kp[I * 4 + m]) : "r"(pack_word(acc, I, m)));
            else kp[I * 4 + m] = GAPB == 2 ? bf2_add(pack_word(acc, I, m), kp[I * 4 + m]) : pack_word(acc, I, m);
        }
    }
    if (n != at) return;
    const uint32_t ro = c.r_off + (c.zero >> n), rx = c.xbuf + ro, rb = c.bar + B_FFULL + ro;
    st_async(rx + (I / 3) * X_UNIT + (I % 3) * X_CH, kp[I * 4], kp[I * 4 + 1], kp[I * 4 + 2], kp[I * 4 + 3], rb);
}
template <int I, bool H = true, int BH = B_HFULL>
__device__ __forceinline__ void send_half(const uint32_t (&p)[12], const Ctx& c, int n = 0) {
    const uint32_t ro = c.r_off + (c.zero >> n), rx = c.xbuf + ro, rb = c.bar + (H ? BH : B_FFULL) + ro;
    st_async(rx + (H ? 2 * X_UNIT : 0) + I * X_CH, p[I * 4], p[I * 4 + 1], p[I * 4 + 2], p[I * 4 + 3], rb);
}
template <int I0, int N>
__device__ __forceinline__ void fin_pack(float (&acc)[48], uint32_t (&pk)[N * 4]) {
    fence_regs(acc);
#pragma unroll
    for (int i = 0; i < N * 4; ++i) {
        pk[i] = pack_word(acc, I0 + (i >> 2), i & 3);
        asm volatile("" : "+r"(pk[i]));
    }
}
template <int N>
__device__ __forceinline__ void fin_load(uint32_t (&v)[N * 4], const Ctx& c, int off) {
#pragma unroll
    for (int i = 0; i < N; ++i)
        asm volatile("ld.shared.v4.b32 {%0, %1, %2, %3}, [%4];"
                     : "=r"(v[i * 4 + 0]), "=r"(v[i * 4 + 1]), "=r"(v[i * 4 + 2]), "=r"(v[i * 4 + 3])
                     : "r"(c.xbuf + off + (i / 3) * X_UNIT + (i % 3) * X_CH) : "memory");
}
template <int N>
__device__ __forceinline__ void fin_store(uint32_t (&pk)[N * 4], const uint32_t (&v)[N * 4], const Ctx& c, int off, int sbar) {
#pragma unroll
    for (int i = 0; i < N; ++i) {
#pragma unroll
        for (int j = i * 4; j < i * 4 + 4; ++j) asm volatile("add.rn.bf16x2 %0, %0, %1;" : "+r"(pk[j]) : "r"(v[j]));
        asm volatile("st.shared.v4.b32 [%0], {%1, %2, %3, %4};"
                     ::"r"(c.xbuf + off + (i / 3) * X_UNIT + (i % 3) * X_CH), "r"(pk[i * 4]), "r"(pk[i * 4 + 1]), "r"(pk[i * 4 + 2]),
                       "r"(pk[i * 4 + 3]) : "memory");
    }
    if (sbar >= 0) mbar_arrive_warp(c.bar + sbar);
}

__device__ __forceinline__ void pin(const uint32_t* r, const Ctx& c) {
    asm volatile("{\n\t.reg .pred q;\n\tsetp.ne.u32 q, %12, 7;\n\t@q bra.uni PIN_SKIP;\n\t"
                 "st.volatile.shared.v4.b32 [%13], {%0, %1, %2, %3};\n\tst.volatile.shared.v4.b32 [%13], {%4, %5, %6, %7};\n\t"
                 "st.volatile.shared.v4.b32 [%13], {%8, %9, %10, %11};\n\tPIN_SKIP:\n\t}"
                 ::"r"(r[0]), "r"(r[1]), "r"(r[2]), "r"(r[3]), "r"(r[4]), "r"(r[5]), "r"(r[6]), "r"(r[7]), "r"(r[8]), "r"(r[9]),
                   "r"(r[10]), "r"(r[11]), "r"(c.wg), "r"(c.bar) : "memory");
}
__device__ __forceinline__ void pin4(const uint32_t* r, const Ctx& c) {
    asm volatile("{\n\t.reg .pred q;\n\tsetp.eq.u32 q, %4, 7;\n\t@q st.volatile.shared.v4.b32 [%5], {%0, %1, %2, %3};\n\t}"
                 ::"r"(r[0]), "r"(r[1]), "r"(r[2]), "r"(r[3]), "r"(c.wg), "r"(c.bar) : "memory");
}
__device__ __forceinline__ void acc_add(float& d, float x, float k) {
    asm volatile("fma.rn.f32 %0, %1, %2, %0;" : "+f"(d) : "f"(x), "f"(k));
}
__device__ __forceinline__ void acc_scale_add(float& d, float k, float x) {
    asm volatile("fma.rn.f32 %0, %0, %2, %1;" : "+f"(d) : "f"(x), "f"(k));
}
template <int RANK, int I0 = 0, int I1 = 24>
__device__ __forceinline__ void mid_row(float (&b)[48], const float (&k)[48], uint32_t (&ps)[12], uint32_t (&pk)[12],
                                        float f = -2.f) {
#pragma unroll
    for (int i = I0; i < I1; ++i) {
        const int ch = i >> 2, o = ((ch % 3) * 4 + (i & 3)) * 4 + (ch / 3) * 2;
        acc_scale_add(b[o], f, k[o]);
        acc_scale_add(b[o + 1], f, k[o + 1]);
        uint32_t& dst = (i / 12 == RANK) ? pk[i % 12] : ps[i % 12];
        dst = pack_bf16(b[o], b[o + 1]);
        asm volatile("" : "+r"(dst));
    }
}
template <int RANK>
__device__ __forceinline__ void mid_row2(float (&b)[48], const float (&k)[48], uint32_t (&ps)[12], uint32_t (&pk)[12], uint32_t (&kp)[24]) {
#pragma unroll
    for (int j = 0; j < 24; ++j) {
        const int i = EPK & 16 ? (j >> 1) + 12 * (j & 1) : (j + 12 - 12 * RANK) % 24;
        const int ch = i >> 2, o = ((ch % 3) * 4 + (i & 3)) * 4 + (ch / 3) * 2;
        const bool keep = i / 12 == RANK;
        uint32_t& dst = keep ? pk[i % 12] : ps[i % 12];
        if (!((PKH >> (keep ? 0 : 1)) & 1)) {
            acc_scale_add(b[o], -2.f, k[o]);
            acc_scale_add(b[o + 1], -2.f, k[o + 1]);
        }
        if (!((PKH & EPK) >> (keep ? 0 : 1) & 1)) dst = pack_bf16(b[o], b[o + 1]);
        if (!keep && (PKH & 2)) {
            kp[i] = pack_bf16(k[o], k[o + 1]);
            asm volatile("" : "+r"(kp[i]));
            dst = bf2_fma<0xc000c000u>(dst, kp[i]);
        }
        asm volatile("" : "+r"(dst));
    }
}
template <int RANK>
__device__ __forceinline__ void pack_k(const float (&k)[48], uint32_t (&kp)[24]) {
#pragma unroll
    for (int i = 0; i < 24; ++i) {
        if (i / 12 != RANK && (PKH & 2)) continue;
        kp[i] = pack_word(k, i >> 2, i & 3);
        asm volatile("" : "+r"(kp[i]));
    }
}
template <int RANK>
__device__ __forceinline__ void fix_hk(uint32_t (&hk)[12], const uint32_t (&kp)[24]) {
    if (PKH & 1) {
#pragma unroll
        for (int i = 0; i < 12; ++i) asm volatile("fma.rn.bf16x2 %0, %0, %2, %1;" : "+r"(hk[i]) : "r"(kp[RANK * 12 + i]), "r"(0xc000c000u));
    }
}
template <int I0, int I1>
__device__ __forceinline__ void acc_add_n(float (&d)[48], const float (&x)[48], float k) {
#pragma unroll
    for (int i = I0; i < I1; ++i) acc_add(d[i], x[i], k);
}

template <int RANK, bool LAST, int I0, int I1>
__device__ __forceinline__ void acc_add_pk(float (&d)[48], const float (&x)[48], float k, uint32_t (&ps)[12], uint32_t (&pk)[12]) {
    if (LAST || !(EPK & 3)) { acc_add_n<I0, I1>(d, x, k); return; }
#pragma unroll
    for (int j = I0 / 2; j < I1 / 2; ++j) {
        const int i = EPK & 8 ? (j >> 1) + 12 * (j & 1) : (j + 12 * ((EPK >> 2 ^ RANK) & 1)) % 24;
        const int ch = i >> 2, o = ((ch % 3) * 4 + (i & 3)) * 4 + (ch / 3) * 2;
        const bool keep = i / 12 == RANK;
        uint32_t& dst = keep ? pk[i % 12] : ps[i % 12];
        acc_add(d[o], x[o], k);
        acc_add(d[o + 1], x[o + 1], k);
        if ((PKH & EPK) >> (keep ? 0 : 1) & 1) {
            dst = pack_bf16(d[o], d[o + 1]);
            asm volatile("" : "+r"(dst));
        }
    }
}

#define LOCK 1
__device__ __forceinline__ void stagger_lead(const Ctx& c, uint32_t id) {
    if (LOCK) {
        asm volatile("{\n\t.reg .pred p;\n\tsetp.eq.u32 p, %1, 0;\n\t@p bar.sync %0, 256;\n\t}" ::"r"(id), "r"(c.wg) : "memory");
        return;
    }
    asm volatile("{\n\t.reg .pred p;\n\tsetp.eq.u32 p, %1, 0;\n\t@p bar.arrive %0, 256;\n\t}" ::"r"(id), "r"(c.wg) : "memory");
}
__device__ __forceinline__ void stagger_lag(const Ctx& c, uint32_t id) {
    asm volatile("{\n\t.reg .pred p;\n\tsetp.ne.u32 p, %1, 0;\n\t@p bar.sync %0, 256;\n\t}" ::"r"(id), "r"(c.wg) : "memory");
}

template <int ID, int WG, bool ARR = false>
__device__ __forceinline__ void lock(const Ctx& c) {
    if (ARR) asm volatile("{\n\t.reg .pred p;\n\tsetp.eq.u32 p, %0, %1;\n\t@p bar.arrive %2, 256;\n\t}" ::"r"(c.wg), "n"(WG), "n"(ID) : "memory");
    else if (WG == 0) asm volatile("{\n\t.reg .pred p;\n\tsetp.eq.u32 p, %0, 0;\n\t@p bar.sync %1, 256;\n\t}" ::"r"(c.wg), "n"(ID) : "memory");
    else asm volatile("{\n\t.reg .pred p;\n\tsetp.ne.u32 p, %0, 0;\n\t@p bar.sync %1, 256;\n\t}" ::"r"(c.wg), "n"(ID) : "memory");
}
#define LA0 1319
#define LB0 9999
#define LC0 9999
#define LA1 LA0
#define LB1 LB0
#define LC1 LC0
#define LA (RANK == 0 ? LA0 : LA1)
#define LB (RANK == 0 ? LB0 : LB1)
#define LC (RANK == 0 ? LC0 : LC1)
#define LORD(p) ((p) >= 24 ? (p) - 24 : (p) + 8)
#define LWRAP(L) (LORD((L) % 100) < LORD((L) / 100))
#define LK(p)                                                                        \
    do {                                                                             \
        if (LA / 100 == (p)) lock<1, 1>(c);                                          \
        if (LB / 100 == (p)) lock<2, 1>(c);                                          \
        if (LC / 100 == (p)) lock<3, 1>(c);                                          \
        if (LA % 100 == (p)) lock<1, 0>(c);                                          \
        if (LB % 100 == (p)) lock<2, 0>(c);                                          \
        if (LC % 100 == (p)) lock<3, 0>(c);                                          \
    } while (0)
#define DEFM 0
#define M1O 0x012
#define M1O0 M1O
#define MO(i) (((RANK == 0 ? M1O0 : M1O) >> (8 - 4 * (i))) & 3)
#define QHW 1
#define CPY 0
#define LDP 0
#define DUPL 0
#define PQ0 0
#define PQ1 0
#define TIE0 0
#define TIE1 0
#define WA 0
#define WB 0
#define PKF (AT(23) == PKSLOT)
#define PROBE 0
#define PAPOS 0
#define PPOS 1
#define CS1 16
#define EPI 0
#define WTOP 1
#define FT_BASE 538
template <int RANK, bool LAST>
__device__ __forceinline__ void phase1b(Ctx& c, float (&accS)[48], float (&accK)[48], float (&accC)[48],
                                        uint32_t (&d0)[24], uint32_t (&d1)[24], const uint32_t (&d2)[24],
                                        const uint32_t (&u)[24], uint32_t (&qd)[12], uint32_t (&qh)[12],
                                        uint32_t (&hs)[12], uint32_t (&hk)[12]) {
    uint32_t pa_ = 0;
    if ((PROBE & 1) && PAPOS == 0) pa_ = mbar_try(c.bar + B_FULLA, LAST ? (NIT - 1) & 1 : c.k & 1);
    if (WTOP == 1) wgmma_wait<0>();
    fence_regs(accS);
    fence_regs(accC);
#pragma unroll
    for (int i = 0; i < 48; ++i)
        asm volatile("fma.rn.f32 %0, %1, %2, %3;" : "=f"(accK[i]) : "f"(accS[i]), "f"(RANK == 0 ? 1.f / 3.f : -4.f / 3.f), "f"(accC[i]));
    constexpr float CF = RANK == 0 ? -1.f / 6.f : -1.f / 3.f;
    if (DUPL) make_dup(qd, d1, c, MO(0));
    mma3d(accK, d1, qd, c, 1, MO(0), -1);
    sb(c);
    if ((PROBE & 1) && PAPOS == 1) pa_ = mbar_try(c.bar + B_FULLA, LAST ? (NIT - 1) & 1 : c.k & 1);
    if (!LAST) LK(24);
    make_dup(qd, d1, c, MO(1));
    mma3d(accK, d1, qd, c, 1, MO(1), -1);
    sb(c);
    if ((PROBE & 1) && PAPOS == 2) pa_ = mbar_try(c.bar + B_FULLA, LAST ? (NIT - 1) & 1 : c.k & 1);
    if (!LAST) LK(26);
    acc_add_pk<RANK, LAST, 0, CS1>(accC, accS, CF, hs, hk);
    if (PROBE & 16) sb(c);
    if (__builtin_expect(!pa_, PROBE & 1 ? 0 : 1)) mbar_wait(c.bar + B_FULLA, LAST ? (NIT - 1) & 1 : c.k & 1);
    if (WA == 1 && !LAST && c.k == 0) mbar_wait(c.bar + B_FULLA, 0);
    if (WA) sb(c);
    wgmma_wait<1>();
    if (LDP == 1) sb(c);
    if (LDP < 2) {
        if (RANK == 0 && !LAST) ld_chunk(d1, c, SL4, 0);
        else ld_chunk(d0, c, SL0, 0);
    }
    make_dup(qd, d1, c, MO(2));
    mma3d(accK, d1, qd, c, 1, MO(2), -1);
    sb(c);
    if (!LAST) LK(28);
    if (LDP == 2) {
        if (RANK == 0 && !LAST) ld_chunk(d1, c, SL4, 0);
        else ld_chunk(d0, c, SL0, 0);
    }
    if (LAST && (EPI & 2)) ld_chunk(d0, c, SL0, 1);
    acc_add_pk<RANK, LAST, CS1, 48>(accC, accS, CF, hs, hk);
    sb(c);
    wgmma_wait<QHW>();
    if (LDP == 3) {
        if (RANK == 0 && !LAST) ld_chunk(d1, c, SL4, 0);
        else ld_chunk(d0, c, SL0, 0);
    }
    if (LAST && (EPI & 1) && !(EPI & 2)) ld_chunk(d0, c, SL0, 1);
    if (LAST && (EPI & 1)) { ld_chunk(d0, c, SL0, 2); sb(c); }
    if (RANK == 0 && !LAST) make_quads<4>(qh, d1, d2, u, 0);
    else make_quads<0>(qh, d0, d2, u, 0);
    sb(c);
}

#define WFA 1
#define P1MC 1
#define P2MC 6
#define WF1C 0
template <int RANK>
__device__ __forceinline__ void consumer(Ctx& c) {
    float accS[48], accK[48], accC[48];
    uint32_t d0[24], d1[24], d2[24], u[24];
    uint32_t qd[12];
#pragma unroll
    for (int i = 0; i < 48; ++i) { accS[i] = 0.f; accC[i] = 0.f; }
    {
        uint32_t qa[12], qe[12];
#define PRO 126
        if ((PRO & 1) || ((PRO & 32) && c.wg)) {
            mbar_wait(c.wready, 0);
            if (!WF1C) asm volatile("fence.proxy.async.shared::cta;" ::: "memory");
            TL(18);
        }
        mbar_wait(c.bar + B_FULL0, 0);
        c.rk = RANK;
        sbz(c);
        const uint32_t xo = (uint32_t)(OFF_X - OFF_IN) - c.wg * (4 * IN_ROW - X_BYTES);
        uint32_t (&d3)[24] = PRO & 4 ? d0 : u;
        ld_chunk_t<0, 0>(d1, c, c.ua + xo, 0);
        ld_chunk(d3, c, SL3, 0);
#define PLD 1
        if (PLD < 2) {
            ld_chunk_t<0, 1>(d1, c, c.ua + xo, 0);
            ld_chunk(d3, c, SL3, 1);
        }
        if (PLD < 1) {
            ld_chunk_t<0, 2>(d1, c, 0, xo + 2 * IN_SLAB - IN_B);
            ld_chunk(d3, c, SL3, 2);
        }
        if (PRO & 2) {
#pragma unroll
            for (int kc = 0; kc < 3; ++kc) {
                if (kc == 1 && PLD == 2) {
                    ld_chunk_t<0, 1>(d1, c, c.ua + xo, 0);
                    ld_chunk(d3, c, SL3, 1);
                }
                if (kc == 1 && PLD) {
                    ld_chunk_t<0, 2>(d1, c, 0, xo + 2 * IN_SLAB - IN_B);
                    ld_chunk(d3, c, SL3, 2);
                }
                if (kc == 2 && (PRO & 64)) {
                    mbar_wait(c.bar + B_FULLC, 0);
                    ld_chunk(d2, c, SL2, 0);
                }
#pragma unroll
                for (int i = kc * 8; i < kc * 8 + 8; ++i) u[i] = bf2_sub(d3[i], d1[i]);
                make_dup(qe, u, c, kc);
                if (kc == 0 && (PRO & 32) && !c.wg) {
                    TL(18);
                    mbar_wait(c.wready, 0);
                    asm volatile("fence.proxy.async.shared::cta;" ::: "memory");
                }
                if (kc == 0) TL(19);
                mma3d(accS, u, qe, c, 3, kc);
                sb(c);
            }
        } else {
#pragma unroll
            for (int i = 0; i < 24; ++i) u[i] = bf2_sub(d3[i], d1[i]);
#pragma unroll
            for (int kc = 0; kc < 3; ++kc) make_dup(qe, u, c, kc);
            if (!(PRO & 1)) {
                TL(18);
                mbar_wait(c.wready, 0);
                if (!WF1C) asm volatile("fence.proxy.async.shared::cta;" ::: "memory");
            }
            TL(19);
#pragma unroll
            for (int kc = 0; kc < 3; ++kc) mma3d(accS, u, qe, c, 3, kc);
        }
        if (!(PRO & 64)) mbar_wait(c.bar + B_FULLC, 0);
        if (!(P1MC & 2) && !(PRO & 8)) mbar_wait(c.wready + (P2MC ? 32 : 16), 0);
        if (!(PRO & 64)) ld_chunk(d2, c, SL2, 0);
        if (!(PRO & 4)) ld_chunk(d0, c, SL3, 0);
        ld_chunk(d2, c, SL2, 1);
        if (!(PRO & 4)) ld_chunk(d0, c, SL3, 1);
        else ld_chunk(d2, c, SL2, 2);
        if (!(P1MC & 2) && (PRO & 8)) mbar_wait(c.wready + (P2MC ? 32 : 16), 0);
#pragma unroll
        for (int kc = 0; kc < 3; ++kc) {
            if (kc == 1 && !(PRO & 4)) { sb(c); ld_chunk(d2, c, SL2, 2); ld_chunk(d0, c, SL3, 2); }
#pragma unroll
            for (int i = kc * 8; i < kc * 8 + 8; ++i) {
                asm volatile("sub.rn.bf16x2 %0, %1, %0;" : "+r"(d0[i]) : "r"(d2[i]));
                asm volatile("fma.rn.bf16x2 %0, %0, %2, %1;" : "+r"(d1[i]) : "r"(d0[i]), "r"(0x40004000u));
                asm volatile("fma.rn.bf16x2 %0, %0, %2, %1;" : "+r"(d0[i]) : "r"(u[i]), "r"(0x3fc03fc0u));
            }
            make_dup(qa, d0, c, kc);
            mma3d(accC, d0, qa, c, 2, kc);
            if (PRO & 16) sb(c);
        }
        mbar_arrive_warp(c.bar + B_EMPTYB);
        if (!DUPL) make_dup(qd, d1, c, MO(0));
        if (LWRAP(LA)) lock<1, 1>(c);
        if (LWRAP(LB)) lock<2, 1>(c);
        if (LWRAP(LC)) lock<3, 1>(c);
        if (WA == 2) mbar_wait(c.bar + B_FULLA, 0);
        if ((P2MC || (P1MC & 2)) && !WFA) mbar_wait(c.wready + 16, 0);
        wgmma_wait<0>();
        c.k = c.zero;
        TL(23);
    }
    constexpr int KA = RANK == 0 ? 4 : 0, KB = 4 - KA;
    constexpr int SA = RANK == 0 ? SL4 : SL0, SB = RANK == 0 ? SL0 : SL4;
    uint32_t (&ea)[24] = RANK == 0 ? d1 : d0;
    uint32_t (&eb)[24] = RANK == 0 ? d0 : d1;
#pragma unroll 1
    while (c.k < NIT - 1) {
#define par(n) ((c.k + (c.zero >> n)) & 1)
        uint32_t qa[12], qb[12], qe[12], qh[12], hs[12], hk[12];
        uint32_t hv[12], pa[12], pb[12], va[12], vb[12], kp[24], pb_ = 0, ph_ = 0, pf_ = 0;
        phase1b<RANK, false>(c, accS, accK, accC, d0, d1, d2, u, qd, qh, hs, hk);
#define AT(i) (int)(((RANK == 0 ? (i < 16 ? PLA0 : PLB0) : (i < 16 ? PLA1 : PLB1)) >> (60 - 4 * (i & 15))) & 15)
#define SLOT(n)                                                                                   \
        if (n < 12) { LK(2 * (n)); }                                                              \
        if (AT(2) == n && FMODE != 1) mbar_wait(c.bar + B_FULL0 + FMODE * 8, par(n));             \
        if (PPOS == 0) { PROBES(n) } if (AT(5) == n && __builtin_expect(!pb_, PROBE & 2 ? 0 : 1)) mbar_wait(c.bar + B_FULLB, par(n));                         \
        if (!(MRG & 1) && AT(14) == n && __builtin_expect(!ph_, PROBE & 4 ? 0 : 1)) mbar_wait(c.bar + B_HFULL, par(n));                                      \
        if (AT(22) == n && __builtin_expect(!pf_, PROBE & 8 ? 0 : 1)) mbar_wait(c.bar + B_FFULL, par(n));                                      \
        if (n == 2) mbar_arrive_warp(c.bar + B_EMPTYE);                                           \
        if (n == 5 && !(MRG & 2)) mbar_arrive_warp(c.bar + B_EMPTYF);                                           \
        if (n == EBSLOT) mbar_arrive_warp(c.bar + B_EMPTYB);                                      \
        if (!LLATE(n)) { LOADS(n) }                                                               \
        if (!LATE(n)) { STORES(n) }                                                               \
        if (PPOS == 1) { PROBES(n) }
#define PROBES(n)                                                                                 \
        if ((PROBE & 2) && AT(5) == n + 1) pb_ = mbar_try(c.bar + B_FULLB, par(n));              \
        if ((PROBE & 4) && AT(14) == n + 1) ph_ = mbar_try(c.bar + B_HFULL, par(n));              \
        if ((PROBE & 8) && AT(22) == n + 1) pf_ = mbar_try(c.bar + B_FFULL, par(n));
#define LOADS(n)                                                                                  \
        if (AT(0) == n) ld_chunk(ea, c, SA, 1);                                                   \
        if (AT(1) == n) ld_chunk(ea, c, SA, 2);                                                   \
        if (AT(2) == n) ld_chunk(eb, c, SB, 0);                                                   \
        if (AT(3) == n) ld_chunk(eb, c, SB, 1);                                                   \
        if (AT(4) == n) ld_chunk(eb, c, SB, 2);                                                   \
        if (AT(5) == n) ld_chunk(u, c, SL3, 0);                                                   \
        if (AT(6) == n) ld_chunk(d2, c, SL2, 0);                                                  \
        if (AT(7) == n) ld_chunk(u, c, SL3, 1);                                                   \
        if (AT(8) == n) ld_chunk(d2, c, SL2, 1);                                                  \
        if (AT(9) == n) ld_chunk(u, c, SL3, 2);                                                   \
        if (AT(10) == n) ld_chunk(d2, c, SL2, 2);                                                 \
        if (AT(14) == n) fin_load<3>(hv, c, 2 * X_UNIT);                                          \
        if (AT(22) == n) fin_load<3>(va, c, 0);                                                   \
        if (AT(24) == n) fin_load<3>(vb, c, X_UNIT);
#define STORES(n)                                                                                 \
        if (n == PKSLOT && PKF) { fin_pack<0, 3>(accK, pa); fin_pack<3, 3>(accK, pb); if (AT(23) != n) pin(pa, c); if (AT(25) != n) pin(pb, c); } \
        if (AT(15) == n) fin_store<3>(hk, hv, c, 2 * X_UNIT, B_SH);                               \
        if (AT(23) == n) fin_store<3>(pa, va, c, 0, -1);                                          \
        if (AT(25) == n) fin_store<3>(pb, vb, c, X_UNIT, B_SF);                                   \
        if (LLATE(n) && !LLATE2(n)) { LOADS(n) }                                                  \
        if (AT(11) == n) send_half<0, true, (MRG & 1) ? B_FULLB : B_HFULL>(hs, c, n);                                                  \
        if (AT(12) == n) send_half<1, true, (MRG & 1) ? B_FULLB : B_HFULL>(hs, c, n);                                                  \
        if (AT(13) == n) send_half<2, true, (MRG & 1) ? B_FULLB : B_HFULL>(hs, c, n);                                                  \
        send_acc<0>(accS, kp, c, n, AT(16), SPK);                                          \
        send_acc<3>(accS, kp, c, n, AT(17), SPK);                                          \
        send_acc<1>(accS, kp, c, n, AT(18), SPK);                                          \
        send_acc<4>(accS, kp, c, n, AT(19), SPK);                                          \
        send_acc<2>(accS, kp, c, n, AT(20), SPK);                                          \
        send_acc<5>(accS, kp, c, n, AT(21), SPK);                                          \
        if (LLATE(n) && LLATE2(n)) { LOADS(n) }                                                   \
        if (n == PKSLOT && !PKF) { fin_pack<0, 3>(accK, pa); fin_pack<3, 3>(accK, pb); pin(pa, c); pin(pb, c); }
#define QW(n, Q)                                                                     \
        if (LATE(n)) { Q; sb(c); STORES(n); sb(c); wgmma_wait<1 + NW(n)>(); FTW(n); }        \
        else if (EQ(n)) { Q; sb(c); wgmma_wait<1 + NW(n)>(); FTW(n); } else { sb(c); wgmma_wait<1 + NW(n)>(); FTW(n); Q; } \
        if (PPOS == 2) { PROBES(n) }                                                              \
        LK(2 * (n) + 1);
#define P1(g, q)                                                                                  \
        SLOT(g + 5);                                                                              \
        if (PG(g) < 4) {                                                                          \
            QW(g + 5, (make_mid<true, (((RANK == 0 ? TIE0 : TIE1) >> (PG(g) & 3)) & 1) != 0>(q, d1, d2, u, PG(g) & 3, u, c.wg)));                                 \
            mma3(accC, q, c, 2, PG(g) & 3, g == 0);                                               \
        } else {                                                                                  \
            QW(g + 5, make_dup(qe, u, c, PG(g) & 3));                                             \
            mma3d(accS, u, qe, c, 3, PG(g) & 3, M1FIRST);                                         \
        }
        if (!GAPB) {
            wgmma_wait<0>();
            fence_regs(accK);
            if (!DEFM) {
                mid_row<RANK>(accC, accK, hs, hk);
                pin(hk, c);
                SLOT(15);
            } else {
                LOADS(15);
            }
            sbk(c);
            acc_add_n<0, 48>(accS, accK, 1.f);
            mma3(accS, qh, c, KA, 0, false);
            sb(c);
            if (DEFM) {
                mid_row<RANK>(accC, accK, hs, hk);
                pin(hk, c);
                STORES(15);
                sb(c);
            }
        } else {
            mma3(accS, qh, c, KA, 0, false);
            LK(30);
            wgmma_wait<1>();
            LK(31);
            fence_regs(accK);
            LOADS(15);
            sbk(c);
            if (GAPB == 2) mid_row2<RANK>(accC, accK, hs, hk, kp);
            else mid_row<RANK>(accC, accK, hs, hk);
            pin(hk, c);
            STORES(15);
            sb(c);
        }
#define PK_(n, e) if (GAPB == 2 && KPS == n && KPE == e) pack_k<RANK>(accK, kp); if (GAPB == 2 && HKS == n && KPE == e) fix_hk<RANK>(hk, kp);
        PK_(0, 2)
        SLOT(0);
        PK_(0, 1)
        make_quads<KA>(qa, ea, d2, u, 1);
        PK_(0, 0)
        LK(1);
        mma3(accS, qa, c, KA, 1, false);
        sb(c);
        PK_(1, 2)
        SLOT(1);
        PK_(1, 1)
        QW(1, make_quads<KA>(qb, ea, d2, u, 2); PK_(1, 0));
        mma3(accS, qb, c, KA, 2, false);
        sb(c);
        PK_(2, 2)
        SLOT(2);
        PK_(2, 1)
        QW(2, make_quads<KB>(qa, eb, d2, u, 0); PK_(2, 0));
        if (WB) mbar_wait(c.bar + B_FULLB, par(2));
        if (WB == 2) mbar_wait(c.bar + B_HFULL, par(2));
        if (GAPB == 1) {
            wgmma_wait<0>();
            fence_regs(accS);
            acc_add_n<0, 48>(accS, accK, 1.f);
        }
        mma3(accK, qa, c, KB, 0, false);
        sb(c);
        PK_(3, 2)
        SLOT(3);
        PK_(3, 1)
        QW(3, make_quads<KB>(qb, eb, d2, u, 1); PK_(3, 0));
        mma3(accK, qb, c, KB, 1, false);
        sb(c);
        PK_(4, 2)
        SLOT(4);
        QW(4, make_quads<KB>(qa, eb, d2, u, 2));
        mma3(accK, qa, c, KB, 2, false);
        sb(c);
        P1(0, qb);

        sb(c);
        P1(1, qa);

        sb(c);
        P1(2, qb);

        sb(c);
        P1(3, qa);

        sb(c);
        P1(4, qb);

        sb(c);
        P1(5, qa);

        sb(c);
        SLOT(11);
        LK(23);
        if (!DUPL) make_dup(qd, d1, c, MO(0));
#pragma unroll
        for (int i = 0; i < 12; ++i)
            if (((RANK == 0 ? PQ0 : PQ1) >> i) & 1) pin4(&d2[(i % 6) * 4], c);
        sbz(c);
        ++c.k;
        if (WA) mbar_wait(c.bar + B_FULLA, c.k & 1);
        if (WTOP == 2) asm volatile("{\n\t.reg .pred q;\n\tsetp.ge.u32 q, %0, %1;\n\t@q bar.arrive 9, 512;\n\t}" ::"r"(c.k), "n"(NIT - 1) : "memory");
        if (WTOP == 3) asm volatile("{\n\t.reg .pred q;\n\tsetp.ge.u32 q, %0, %1;\n\t@q nanosleep.u32 0;\n\t}" ::"r"(c.k), "n"(NIT - 1) : "memory");
        if (WTOP == 4) asm volatile("{\n\t.reg .pred q;\n\tsetp.ge.u32 q, %0, %1;\n\t@q st.volatile.shared.u32 [%2 + 120], %3;\n\t}" ::"r"(c.k), "n"(NIT - 1), "r"(c.bar), "r"(c.vz) : "memory");
        if (WTOP != 1) wgmma_wait<0>();
        TL(1 + c.k);
#undef par
    }
    {
        constexpr uint32_t par = (NIT - 1) & 1;
        uint32_t qa[12], qb[12], qh[12], hs[12], hk[12], v[12];
        constexpr int S0 = 12 - 12 * RANK, K0 = 12 * RANK;
        uint32_t pk[12];
        if (LWRAP(LA)) lock<1, 0, true>(c);
        if (LWRAP(LB)) lock<2, 0, true>(c);
        if (LWRAP(LC)) lock<3, 0, true>(c);
        phase1b<RANK, true>(c, accS, accK, accC, d0, d1, d2, u, qd, qh, hs, hk);
#define TE(n)
        TE(4);
        mma3(accS, qh, c, 0, 0, RANK == 0);
        if (EPI & 1) {
            sb(c);
            make_quads<0>(qa, d0, d2, u, 1);
            mma3(accS, qa, c, 0, 1, false);
            sb(c);
            make_quads<0>(qb, d0, d2, u, 2);
            mma3(accS, qb, c, 0, 2, false);
            wgmma_wait<3>();
            fence_regs(accK);
            mid_row<RANK, S0, S0 + 12>(accC, accK, hs, hk);
            send_half<0>(hs, c);
            send_half<1>(hs, c);
            send_half<2>(hs, c);
            sb(c);
        } else {
            wgmma_wait<1>();
            ld_chunk(d0, c, SL0, 1);
            ld_chunk(d0, c, SL0, 2);
            fence_regs(accK);
            mid_row<RANK, S0, S0 + 12>(accC, accK, hs, hk);
            send_half<0>(hs, c);
            send_half<1>(hs, c);
            send_half<2>(hs, c);
            sb(c);
            make_quads<0>(qa, d0, d2, u, 1);
            mma3(accS, qa, c, 0, 1, false);
            make_quads<0>(qb, d0, d2, u, 2);
            mma3(accS, qb, c, 0, 2, false);
        }
        TE(5);
        mid_row<RANK, K0, K0 + 12>(accC, accK, hs, hk);
        mbar_wait(c.bar + B_FULLB, par);
        TE(6);
        wgmma_wait<0>();
        TE(7);
        fence_regs(accS);
        mid_row<RANK, S0, S0 + 12>(accS, accK, hs, pk, 1.f);
        send_half<0, false>(hs, c);
        send_half<1, false>(hs, c);
        send_half<2, false>(hs, c);
        TE(8);
        mbar_wait(c.bar + B_HFULL, MRG & 1 ? 0 : par);
        TE(9);
        fin_load<3>(v, c, 2 * X_UNIT);
        mid_row<RANK, K0, K0 + 12>(accS, accK, hs, pk, 1.f);
        fin_store<3>(hk, v, c, 2 * X_UNIT, B_SH);
        mbar_wait(c.bar + B_FFULL + c.zero, par);
        TE(10);
        fin_load<3>(v, c, 0);
        fin_store<3>(pk, v, c, 0, B_SF);
        TL(17);
    }
}

__device__ __forceinline__ void wt_load(uint32_t (&g)[36], uint32_t unit, int lane) {
    const uint32_t src = unit + (lane >> 2) * 192 + ((lane & 3) << 4);
#pragma unroll
    for (int i = 0; i < 9; ++i)
        asm volatile("ld.shared.v4.b32 {%0, %1, %2, %3}, [%4];"
                     : "=r"(g[i * 4]), "=r"(g[i * 4 + 1]), "=r"(g[i * 4 + 2]), "=r"(g[i * 4 + 3])
                     : "r"(src + (i / 3) * 64 + (i % 3) * 2 * W_COMP) : "memory");
}
__device__ __forceinline__ void stsm(uint32_t addr, const uint32_t* v) {
    asm volatile("stmatrix.sync.aligned.m8n8.x4.shared.b16 [%0], {%1, %2, %3, %4};"
                 ::"r"(addr), "r"(v[0]), "r"(v[1]), "r"(v[2]), "r"(v[3]) : "memory");
}
template <int PART>
__device__ __forceinline__ void wt_store(const uint32_t (&g)[36], uint32_t unit, int lane) {
    const uint32_t dst = unit + (lane & 7) * 64 + ((((lane >> 3) ^ (lane >> 1)) & 3) << 4);
#pragma unroll
    for (int r = 0; r < 3; ++r) {
        const uint32_t *a = &g[r * 12], *b = a + 4, *cc = a + 8;
        uint32_t u1[4], u2[4], u3[4];
#pragma unroll
        for (int i = 0; i < 4; ++i) {
            uint32_t h;
            asm("add.rn.bf16x2 %0, %1, %2;" : "=r"(h) : "r"(a[i]), "r"(cc[i]));
            asm("mul.rn.bf16x2 %0, %1, %2;" : "=r"(h) : "r"(h), "r"(0x3f003f00u));
            asm("fma.rn.bf16x2 %0, %1, %2, %3;" : "=r"(u1[i]) : "r"(b[i]), "r"(0x3f003f00u), "r"(h));
            asm("fma.rn.bf16x2 %0, %1, %2, %3;" : "=r"(u2[i]) : "r"(b[i]), "r"(0xbf00bf00u), "r"(h));
            asm("mul.rn.bf16x2 %0, %1, %2;" : "=r"(h) : "r"(u2[i]), "r"(0xbaabbaabu));
            asm("fma.rn.bf16x2 %0, %0, %1, %2;" : "+r"(u2[i]) : "r"(0x3f2b3f2bu), "r"(h));
            asm("fma.rn.bf16x2 %0, %1, %2, %3;" : "=r"(h) : "r"(a[i]), "r"(0x3e803e80u), "r"(cc[i]));
            asm("fma.rn.bf16x2 %0, %1, %2, %3;" : "=r"(u3[i]) : "r"(h), "r"(0x40004000u), "r"(b[i]));
        }
        if (PART & 1) stsm(dst + r * 512 + CP(3) * W_COMP, u3);
        if (PART & 2) stsm(dst + r * 512 + CP(2) * W_COMP, u2);
        if (PART & 4) stsm(dst + r * 512 + CP(1) * W_COMP, u1);
        if (PART & 8) {
            stsm(dst + r * 512 + CP(0) * W_COMP, a);
            stsm(dst + r * 512 + CP(4) * W_COMP, cc);
        }
    }
}

__device__ __forceinline__ int seq_row(int seg, int row_par, int n) {
    const int q = (seg & 1) ? seg * SEG - 1 + n : seg * SEG + SEG - n;
    return 2 * q + row_par;
}

#define WF2 0
struct XMaps { CUtensorMap m[2]; };
#define xmap xm.m[0]
__global__ void __cluster_dims__(2, 1, 1) __launch_bounds__(384, 1)
conv_kernel(const char* __restrict__ wp, const char* __restrict__ xp,
            const __grid_constant__ XMaps xm, const __grid_constant__ CUtensorMap omap) {
    extern __shared__ uint8_t smem_raw[];
    const uint32_t base = (smem_u32(smem_raw) + 1023u) & ~1023u;
    const uint32_t wbase = base + OFF_W;
    const uint32_t bar_base = base + OFF_BAR;
    const uint32_t wbar_b = bar_base + 256, wready_b = bar_base + 280;

    const int tid = threadIdx.x;
    const int warp = tid >> 5, lane = tid & 31;
    const int rank = blockIdx.x & 1;
    const int cluster = blockIdx.x >> 1;
    const int strip = cluster & 7, seg = cluster >> 3;
    const int fmode = rank ? FMODE1 : FMODE0;
#define WPN 26
#define XPN 0
#define XPR 1
#define XPW 0
    uint32_t c_start;
    {
        const uint32_t t = tid - 96, l = blockIdx.x * 10 + t;
        asm volatile("{\n\t.reg .pred p;\n\tsetp.lt.u32 p, %1, %2;\n\t@p prefetch.global.L2 [%0];\n\t}" ::"l"(wp + l * 128), "r"(t), "n"(WPN) : "memory");
        if (XPN) {
            const uint32_t t2 = tid - 128;
            asm volatile("{\n\t.reg .pred p;\n\tsetp.lt.u32 p, %1, %2;\n\t@p prefetch.global.L2 [%0];\n\t}"
                         ::"l"(xp + (uint32_t)(seq_row(seg, XPW, XPR) * (IMG_W * 192) + (strip * 64 + rank * 32) * 192 + t2 * 128)), "r"(t2), "n"(XPN) : "memory");
        }
    }
    asm volatile("mov.u32 %0, %clock;" : "=r"(c_start) :: "memory");

#define SX(j)
    const int uwarp = __shfl_sync(0xffffffffu, warp, 0);
    const bool el = elect();
#define WPM 0
#define NOF 0
#define PFPOS 0
#define PFBLK
#define NPF 0
#define PFT 400
#define PFS 0
#define PORD 0xc4ab9231
#define PFL 48
    if (NPF && (unsigned)(tid - 128) < NPF * PFL) {
        const int i = (tid - 128) / PFL, e = (PORD >> (i * 4)) & 15;
        const int prow = seq_row(seg, e >> 3, e & 7);
        const char* p = xp + (size_t)prow * (IMG_W * 192) + (strip * 64 + rank * 32) * 192 + (tid - 128 - i * PFL) * 128;
        if (PFT) while ((uint32_t)clock() - c_start < PFT + (warp - 4) * PFS) {}
        asm volatile("prefetch.global.L2 [%0];" ::"l"(p) : "memory");
        if (warp == 4) SX(7);
    }
    if (uwarp == 0 && el) {
        for (int i = 0; i < 3; ++i) mbar_init(wbar_b + i * 8, 1);
        if (!(NOF & 1)) asm volatile("fence.proxy.async.shared::cta;" ::: "memory");
        else asm volatile("fence.mbarrier_init.release.cluster;" ::: "memory");
        const int up = (seg & 1) ^ 1;
        SX(2);
#pragma unroll
        for (int j = 0; j < 3; ++j) {
#pragma unroll
            for (int i = 0; i < 3; ++i)
                asm volatile("cp.async.bulk.shared::cluster.global.mbarrier::complete_tx::bytes [%0], [%1], %2, [%3];"
                             ::"r"(wbase + ((up ? 2 - i : i) * 6 + j) * W_TAP), "l"(wp + (2 * (i * 3 + j) + rank) * W_TAP),
                               "r"(W_TAP), "r"(wbar_b + j * 8) : "memory");
        }
        SX(3);
        for (int j = 0; j < 3; ++j) mbar_expect_tx(wbar_b + j * 8, 3 * W_TAP);
        asm volatile("fence.mbarrier_init.release.cluster;" ::: "memory");
    }
    if (PFPOS == 1) { PFBLK }
#define RT 320
    if (uwarp == 2 && el) {
        for (int i = 0; i < 2; ++i) {
            mbar_init(bar_base + i * 128 + B_FULLA, 3);
            mbar_init(bar_base + i * 128 + B_FULLB, 2);
            mbar_init(bar_base + i * 128 + B_EMPTYE, 4);
            mbar_init(bar_base + i * 128 + B_EMPTYF, 4);
            mbar_init(bar_base + i * 128 + B_EMPTYB, 4);
            mbar_init(bar_base + i * 128 + B_HFULL, 1);
            mbar_init(bar_base + i * 128 + B_FFULL, 1);
            mbar_init(bar_base + i * 128 + B_SH, 4);
            mbar_init(bar_base + i * 128 + B_SF, 4);
            mbar_expect_tx(bar_base + i * 128 + B_HFULL, X_TX);
            mbar_expect_tx(bar_base + i * 128 + B_FFULL, 2 * X_TX);
            if (!WFA) mbar_arrive(bar_base + i * 128 + B_FULLA);
        }
        mbar_init(wready_b, 10);
        mbar_init(wready_b + 8, 4);
        mbar_init(wready_b + 16, WF2 ? 4 : 1);
        mbar_init(wready_b + 24, 4);
        mbar_init(wready_b + 32, 1);
        asm volatile("fence.mbarrier_init.release.cluster;" ::: "memory");
        asm volatile("fence.proxy.async.shared::cta;" ::: "memory");
    }
    if (uwarp == 10 && el) {
        asm volatile("prefetch.tensormap [%0];" ::"l"((uint64_t)(&xmap)) : "memory");
        asm volatile("prefetch.tensormap [%0];" ::"l"((uint64_t)(&xmap + 1)) : "memory");
        for (int i = 0; i < 4; ++i) mbar_init(bar_base + (i >> 1) * 128 + (i & 1) * B_FULLC, 1);
        for (int i = 0; i < 4; ++i) mbar_expect_tx(bar_base + (i >> 1) * 128 + (i & 1) * B_FULLC, (2 - (i & 1)) * IN_ROW);
        asm volatile("fence.mbarrier_init.release.cluster;" ::: "memory");
        if (!(NOF & 2)) asm volatile("fence.proxy.async.shared::cta;" ::: "memory");
    }
    __syncwarp();
    asm volatile("barrier.cluster.arrive.relaxed.aligned;" ::: "memory");
#define RSTEP 150
    if (uwarp == 10 && el) {
#pragma unroll
        for (int i = 0; i < 6; ++i) {
            const int wg = (RORD >> (i * 4 + 2)) & 1, n = (RORD >> (i * 4)) & 3;
            const uint32_t fb = bar_base + wg * 128 + (n == 2 ? B_FULLC : B_FULL0);
            if (i == 0 || RSTEP) while ((uint32_t)clock() - c_start < ROW_DELAY + i * RSTEP) {}
            const uint32_t dst = base + (n == 1 ? OFF_X + wg * X_BYTES : OFF_IN + wg * 4 * IN_ROW + n * 2 * IN_SLAB);
            load_row(dst, dst + (n == 1 ? 2 * IN_SLAB : IN_B - n * IN_SLAB), &xmap, fb, rank, strip, seq_row(seg, wg, n), true);
            if (i < 2) SX(4 + i);
            if (i == 5) SX(6);
        }
    }
    __syncwarp();
#define ST(j)
    ST(0);
    asm volatile("barrier.cluster.wait.aligned;" ::: "memory");
#define RLW 1
#define WX 4
#define HW0 11
#define HW1 9
#define P1M 1
#define P2M 6
#define WF1 0
    if (uwarp < 4 || uwarp == HW0 || uwarp == HW1) {
        uint32_t ga[36];
        const int uw = uwarp < 4 ? uwarp : uwarp == HW0 ? 4 : 5;
        const uint32_t unit = wbase + uw * W_K8;
        ST(1);
        mbar_wait(wbar_b, 0);
        ST(2);
        wt_load(ga, unit, lane);
        __syncwarp();
        wt_store<15>(ga, unit, lane);
        ST(5);
        if (WF1) asm volatile("fence.proxy.async.shared::cta;" ::: "memory");
        mbar_arrive_warp(wready_b);
        ST(6);
    } else if (uwarp < 8) {
        uint32_t ga[36], gb[36], gc[36];
        const uint32_t unit = wbase + (uwarp + 2) * W_K8;
        ST(1);
        mbar_wait(wbar_b + 8, 0);
        wt_load(ga, unit, lane);
        mbar_wait(wbar_b + (uwarp < 6 ? 8 : 16), 0);
        wt_load(gb, unit + 4 * W_K8, lane);
        mbar_wait(wbar_b + 16, 0);
        ST(2);
        wt_load(gc, unit + 8 * W_K8, lane);
        __syncwarp();
        wt_store<P1M>(ga, unit, lane);
        wt_store<P1M>(gb, unit + 4 * W_K8, lane);
        wt_store<P1M>(gc, unit + 8 * W_K8, lane);
        if (WF1) asm volatile("fence.proxy.async.shared::cta;" ::: "memory");
        mbar_arrive_warp(wready_b);
        ST(3);
        if (P2M) {
            wt_store<P2M>(ga, unit, lane);
            wt_store<P2M>(gb, unit + 4 * W_K8, lane);
            wt_store<P2M>(gc, unit + 8 * W_K8, lane);
            mbar_arrive_warp(wready_b + 24);
        }
        ST(4);
        wt_store<15 - P1M - P2M>(ga, unit, lane);
        wt_store<15 - P1M - P2M>(gb, unit + 4 * W_K8, lane);
        wt_store<15 - P1M - P2M>(gc, unit + 8 * W_K8, lane);
        ST(5);
        if (WF2) asm volatile("fence.proxy.async.shared::cta;" ::: "memory");
        mbar_arrive_warp(wready_b + (WF2 ? 16 : 8));
        ST(6);
    }

    if (uwarp >= 8) {
        asm volatile("setmaxnreg.dec.sync.aligned.u32 24;");
        {
            const int wg = uwarp & 1;
            const uint32_t bar = bar_base + wg * 128;
            const int step = (seg & 1) ? 2 : -2;
            if (uwarp < 10) {
                const uint32_t in = base + OFF_IN + wg * 4 * IN_ROW;
                const char* pf = xp + (strip * 64 + rank * 32) * 192;
                int row = seq_row(seg, wg, 0);
#pragma unroll 1
                for (int t = 0; t < NIT; ++t, row += 3 * step) {
#pragma unroll
                    for (int g = 0; g < 3; ++g) {
                        const int sl = g == 2 ? 2 : (g ^ rank ^ 1);
                        const uint32_t fb = bar + (g == 2 ? B_FULLB : B_FULLA);
                        if (g == 1 && (MRG & 2)) mbar_wait_h(bar + B_SH, ~t & 1);
                        else mbar_wait_h(bar + B_EMPTYE + g * 8, t & 1);
                        STAMP(t, 6 + g);
                        if (el) {
                            const bool ld = t < NIT - 1 || sl == 0;
                            if (ld) {
                                if (g == 2) load_row(in + 2 * SL3, in + IN_B + SL3, &xmap, fb, rank, strip, row + 6 * step, true);
                                load_row(in + sl * 2 * IN_SLAB, in + IN_B + sl * IN_SLAB, &xmap, fb, rank, strip, row + (g == 2 ? 5 : 4 * sl) * step, true);
                            }
                            mbar_expect_tx(fb, ld ? (g == 2 ? 2 * IN_ROW + (MRG & 1) * X_TX : IN_ROW) : 0);
                            if (g == 2 && t == 0) mbar_arrive_remote(mapa(fb, rank ^ 1));
                            const int n = 3 * t + g + 1, prow = row + (g + 1 + PF) * step;
                            if (n >= PF0 && n + PF < SEG + 2 && (unsigned)prow < IMG_H)
                                asm volatile("cp.async.bulk.prefetch.L2.global [%0], %1;"
                                             ::"l"(pf + (size_t)prow * (IMG_W * 192)), "r"(32 * 192) : "memory");
#define EPT 0
                            if (EPT && n < 5) {
                                const int e0 = (EPT >> (n * 8 - 8)) & 15, e1 = (EPT >> (n * 8 - 4)) & 15;
                                if (e0) asm volatile("cp.async.bulk.prefetch.L2.global [%0], %1;"
                                                     ::"l"(pf + (size_t)(row + (e0 - 3 * t) * step) * (IMG_W * 192)), "r"(32 * 192) : "memory");
                                if (e1) asm volatile("cp.async.bulk.prefetch.L2.global [%0], %1;"
                                                     ::"l"(pf + (size_t)(row + (e1 - 3 * t) * step) * (IMG_W * 192)), "r"(32 * 192) : "memory");
                            }
                        }
                        __syncwarp();
                        if (g) STAMP(t, 8 + g);
                    }
                }
            } else {
                const uint32_t src = base + OFF_X + wg * X_BYTES;
                const uint32_t r_bar = mapa(bar, rank ^ 1);
                if (wg == 0 && lane < 4)
                    asm volatile("mbarrier.arrive.shared::cta.b64 _, [%0], 4;" ::"r"(bar + (lane >> 1) * 128 + B_EMPTYE + (lane & 1) * 8) : "memory");
                __syncwarp();
                if (wg == RLW) {
                    if (P2M) {
                        mbar_wait(wready_b + 24, 0);
                        asm volatile("fence.proxy.async.shared::cta;" ::: "memory");
                        mbar_arrive_warp(wready_b + 32);
                    }
                    if (!WF2) {
                        mbar_wait(wready_b + 8, 0);
                        asm volatile("fence.proxy.async.shared::cta;" ::: "memory");
                        if (WFA) { if (lane < 2) mbar_arrive(bar_base + lane * 128 + B_FULLA); }
                        else mbar_arrive_warp(wready_b + 16);
                    }
                    if (RLW) ST(7);
                }
                int row = seq_row(seg, wg, 1);
#pragma unroll 1
                for (int t = 0; t < NIT; ++t, row += 3 * step) {
                    const bool last = t == NIT - 1;
                    mbar_wait_h(bar + B_SH, t & 1);
                    STAMP(t, 0);
                    if (el) {
                        asm volatile("fence.proxy.async.shared::cta;" ::: "memory");
                        tma_store_4d(&omap, src + 2 * X_UNIT, 0, strip * 16, rank, row + step, EF(t, 2));
                        asm volatile("cp.async.bulk.commit_group;" ::: "memory");
                        if (!last) {
                            if (!(MRG & 1)) mbar_expect_tx(bar + B_HFULL, X_TX);
                            asm volatile("cp.async.bulk.wait_group.read 0;" ::: "memory");
                            mbar_arrive_remote(r_bar + B_FULLA);
                        }
                    }
                    __syncwarp();
                    STAMP(t, 1);
                    mbar_wait_h(bar + B_SF, t & 1);
                    STAMP(t, 2);
                    if (el) {
                        asm volatile("fence.proxy.async.shared::cta;" ::: "memory");
                        const int orow = row + (last ? 0 : 2 * rank * step);
                        tma_store_4d(&omap, src, 0, strip * 16, last ? rank : 0, orow, EF(t, 0));
                        if (!last) tma_store_4d(&omap, src + X_UNIT, 0, strip * 16, 1, orow, EF(t, 1));
                        asm volatile("cp.async.bulk.commit_group;" ::: "memory");
                        if (!last) mbar_expect_tx(bar + B_FFULL, t == NIT - 2 ? X_TX : 2 * X_TX);
                        asm volatile("cp.async.bulk.wait_group.read 0;" ::: "memory");
                        if (!last) mbar_arrive_remote(r_bar + B_FULLB);
                    }
                    __syncwarp();
                    STAMP(t, 3);
                }
            }
        }
    } else {
        const int wg = uwarp >> 2;
        const int w4 = warp & 3;
        if (RT >= 256) asm volatile("setmaxnreg.inc.sync.aligned.u32 240;");
        ST(7);
        Ctx c;
        c.bar = bar_base + wg * 128;
        c.wdesc = ((wbase & 0x3FFFF) >> 4) | ((uint32_t)(512 >> 4) << 16);
        c.wready = wready_b;
        c.wg = wg;
        c.k = ~0u;
        c.zero = 0;
        c.tlo2 = bar_base + 576 - bar_base * 4;
        c.tlo = 320;
        {
            const int m = lane >> 3, gg = lane & 7, hl = m >> 1;
            const int rho0 = (m & 1) ? (8 * w4 + gg + 2) : (36 + 8 * w4 + gg);
            const int rho1 = rho0 + 2;
            const uint32_t in = base + OFF_IN + wg * 4 * IN_ROW;
            c.ld0 = in + IN_B + rho0 * 32 + ((hl ^ ((rho0 >> 2) & 1)) << 4);
            c.ld1 = in + IN_B + rho1 * 32 + ((hl ^ ((rho1 >> 2) & 1)) << 4);
            c.vz = (rho0 & 2) << 3;
            c.ua = in - 2 * (in + IN_B);
        }
        c.xbuf = base + OFF_X + wg * X_BYTES + (tid & 127) * 16;
        c.r_off = mapa(c.bar, rank ^ 1) - c.bar;
        c.ld0 = __shfl_sync(0xffffffffu, c.ld0, lane);
        c.ld1 = __shfl_sync(0xffffffffu, c.ld1, lane);
        c.xbuf = __shfl_sync(0xffffffffu, c.xbuf, lane);
        TL(1);
        TLC(20);
        if (rank == 0) consumer<0>(c);
        else consumer<1>(c);
        TLC(21);
    }
}

typedef CUresult (*EncodeFn)(CUtensorMap*, CUtensorMapDataType, cuuint32_t, void*, const cuuint64_t*,
                             const cuuint64_t*, const cuuint32_t*, const cuuint32_t*, CUtensorMapInterleave,
                             CUtensorMapSwizzle, CUtensorMapL2promotion, CUtensorMapFloatOOBfill);

}

extern "C" void kernel_launch(void* const* d_in, const int* in_sizes, int n_in, void* d_out, int out_size) {
    (void)in_sizes; (void)n_in; (void)out_size;
    static EncodeFn encode = nullptr;
    if (!encode) {
        void* fn = nullptr;
        cudaDriverEntryPointQueryResult qres;
        cudaGetDriverEntryPoint("cuTensorMapEncodeTiled", &fn, cudaEnableDefault, &qres);
        encode = (EncodeFn)fn;
        cudaFuncSetAttribute(conv_kernel, cudaFuncAttributeMaxDynamicSharedMemorySize, SMEM_BYTES);
    }
    XMaps xm;
    CUtensorMap omap;
    cuuint32_t estr5[5] = {1, 1, 1, 1, 1};
    {
        cuuint64_t dims[5] = {(cuuint64_t)CH, 2, (cuuint64_t)IMG_W / 4, 2, (cuuint64_t)IMG_H};
        cuuint64_t strides[4] = {(cuuint64_t)CH * 2, (cuuint64_t)CH * 2 * 4, (cuuint64_t)CH * 2 * 2,
                                 (cuuint64_t)IMG_W * CH * 2};
        cuuint32_t box[5] = {16, 2, 18, 2, 1};
        encode(&xmap, CU_TENSOR_MAP_DATA_TYPE_BFLOAT16, 5, d_in[0], dims, strides, box, estr5,
               CU_TENSOR_MAP_INTERLEAVE_NONE, CU_TENSOR_MAP_SWIZZLE_32B, PROMO,
               CU_TENSOR_MAP_FLOAT_OOB_FILL_NONE);
        box[0] = 32;
        encode(&xm.m[1], CU_TENSOR_MAP_DATA_TYPE_BFLOAT16, 5, d_in[0], dims, strides, box, estr5,
               CU_TENSOR_MAP_INTERLEAVE_NONE, CU_TENSOR_MAP_SWIZZLE_64B, PROMO,
               CU_TENSOR_MAP_FLOAT_OOB_FILL_NONE);
    }
    {
        cuuint64_t dims[5] = {32, 2, (cuuint64_t)IMG_H * IMG_W / 4, 3, 2};
        cuuint64_t strides[4] = {(cuuint64_t)CH * 2, (cuuint64_t)CH * 2 * 4, 64, (cuuint64_t)CH * 2 * 2};
        cuuint32_t box[5] = {32, 2, 16, 3, 1};
        encode(&omap, CU_TENSOR_MAP_DATA_TYPE_BFLOAT16, 5, d_out, dims, strides, box, estr5,
               CU_TENSOR_MAP_INTERLEAVE_NONE, CU_TENSOR_MAP_SWIZZLE_NONE, CU_TENSOR_MAP_L2_PROMOTION_NONE,
               CU_TENSOR_MAP_FLOAT_OOB_FILL_NONE);
    }
    conv_kernel<<<NUM_CTAS, 384, SMEM_BYTES>>>((const char*)d_in[1], (const char*)d_in[0], xm, omap);
}
```

```cpp
#include <cuda_runtime.h>
#include <cuda_bf16.h>
#include <cuda.h>
#include <stdint.h>

namespace {

#define PFIRST
#define GAPB 2
#define PKH0 3
#define PKH1 PKH0
#define PKH (RANK == 0 ? PKH0 : PKH1)
#define KPS0 2
#define KPS1 KPS0
#define KPS (RANK == 0 ? KPS0 : KPS1)
#define EPK0 11
#define EPK1 EPK0
#define EPK (RANK == 0 ? EPK0 : EPK1)
#define SPK0 15
#define SPK1 SPK0
#define SPK (RANK == 0 ? SPK0 : SPK1)
#define KPE 0
#define HKS 3
#define ST_EF
#define PF 6
#define PF0 5
#define EQ0 0x7fa
#define EQ1 0x7fe
#define PLA0 0xf0223445566ff045ull
#define PLA1 0xff012445566ff045ull
#define PLB0 0x4444459aab000000ull
#define PLB1 0x4444459aab000000ull
#define FMODE0 1
#define FMODE1 1
#define ORD 0
#define FMODE (RANK == 0 ? FMODE0 : FMODE1)
#define LT0 0
#define LT1 0
#define LATE(n) (((RANK == 0 ? LT0 : LT1) >> (n)) & 1)
#define LL0 0x10
#define LL1 0x10
#define LLATE(n) (((RANK == 0 ? LL0 : LL1) >> (n)) & 1)
#define PO0 0x012654
#define PO1 PO0
#define PG(g) (((RANK == 0 ? PO0 : PO1) >> (20 - (g) * 4)) & 7)
#define M1FIRST (PG(1) >= 4 ? PG(1) & 3 : PG(2) >= 4 ? PG(2) & 3 : PG(3) & 3)
#define EBSLOT (PG(2) == 2 ? 8 : PG(3) == 2 ? 9 : 10)
#define NW0 0
#define NW1 NW0
#define NW(n) (((RANK == 0 ? NW0 : NW1) >> (n)) & 1)
#define DEC 1
#define RORD 0x675231
#define PW0 0
#define PW1 1
#define EPO 0x8c04ab9231ull
#define PROMO CU_TENSOR_MAP_L2_PROMOTION_L2_128B
#define ZEND 1
#define HPIN 0
#define LL2 0x20
#define LLATE2(n) ((LL2 >> (n)) & 1)
#define CPT 0x01234
#define CP(k) ((CPT >> (16 - 4 * (k))) & 7)
#define MEF 0
#define DEFW 0
#define PKSLOT 7
#define EQ(n) (((RANK == 0 ? EQ0 : EQ1) >> (n)) & 1)
#define LAG0 6
#define LEAD0 9
#define LAG1 LAG0
#define LEAD1 LEAD0
#define LAGPOS (RANK == 0 ? LAG0 : LAG1)
#define LEADPOS (RANK == 0 ? LEAD0 : LEAD1)
#define LAGK (LEADPOS > 20 ? 1 : LEADPOS >= 12 || LEADPOS < LAGPOS ? 2 : 1)
#define SEND1 4
#define SEND2 6
#define TL(slot)
#define TLC(slot)
constexpr int IMG_H = 512, IMG_W = 512, CH = 96;
constexpr int IN_SLAB = 72 * 32;
constexpr int IN_ROW = 3 * IN_SLAB;
constexpr int SL0 = 0, SL4 = IN_SLAB, SL2 = 2 * IN_SLAB, SL3 = 3 * IN_SLAB, IN_B = 8 * IN_SLAB;
constexpr int W_K8 = 3 * 512;
constexpr int W_TAP = 6 * W_K8;
constexpr int W_COMP = 3 * W_TAP;
constexpr int W_BYTES = 5 * W_COMP;
constexpr int X_CH = 32 * 64;
constexpr int X_UNIT = 3 * X_CH;
constexpr int X_BYTES = 3 * X_UNIT;
constexpr int X_TX = X_UNIT;
constexpr int SEG = 32;
constexpr int NIT = 11;
constexpr int NUM_CTAS = 128;
#define LAY 3
constexpr int OFF_W = LAY == 0 ? 0 : LAY == 1 ? 2 * X_BYTES : LAY == 2 ? 2 * X_BYTES + 8 * IN_ROW : 8 * IN_ROW;
constexpr int OFF_X = LAY == 0 ? W_BYTES : LAY == 3 ? W_BYTES + 8 * IN_ROW : 0;
constexpr int OFF_IN = LAY == 3 ? 0 : LAY == 2 ? 2 * X_BYTES : W_BYTES + 2 * X_BYTES;
constexpr int OFF_BAR = W_BYTES + 2 * X_BYTES + 8 * IN_ROW;
constexpr int SMEM_BYTES = 1024 + OFF_BAR + 1024;
static_assert(SMEM_BYTES <= 232448, "smem");
#define RDEL 400
constexpr uint32_t ROW_DELAY = RDEL;
constexpr int B_FULL0 = 0, B_FULLA = 8, B_FULLB = 16, B_FULLC = 24, B_EMPTYE = 32, B_EMPTYF = 40, B_EMPTYB = 48, B_HFULL = 56,
              B_FFULL = 64, B_SH = 72, B_SF = 80;

__device__ __forceinline__ uint32_t smem_u32(const void* p) {
    return (uint32_t)__cvta_generic_to_shared(p);
}
__device__ __forceinline__ void mbar_init(uint32_t bar, uint32_t count) {
    asm volatile("mbarrier.init.shared::cta.b64 [%0], %1;" ::"r"(bar), "r"(count) : "memory");
}
__device__ __forceinline__ void mbar_expect_tx(uint32_t bar, uint32_t bytes) {
    asm volatile("mbarrier.arrive.expect_tx.shared::cta.b64 _, [%0], %1;" ::"r"(bar), "r"(bytes) : "memory");
}
__device__ __forceinline__ void mbar_arrive(uint32_t bar) {
    asm volatile("mbarrier.arrive.shared::cta.b64 _, [%0];" ::"r"(bar) : "memory");
}
__device__ __forceinline__ void mbar_arrive_warp(uint32_t bar) {
    __syncwarp();
    asm volatile("{\n\t.reg .pred p;\n\telect.sync _|p, 0xffffffff;\n\t@p mbarrier.arrive.shared::cta.b64 _, [%0];\n\t}" ::"r"(bar) : "memory");
}
__device__ __forceinline__ void mbar_arrive_remote(uint32_t rbar) {
    asm volatile("mbarrier.arrive.relaxed.cluster.shared::cluster.b64 _, [%0];" ::"r"(rbar) : "memory");
}
__device__ __forceinline__ void mbar_expect_tx_remote(uint32_t rbar, uint32_t bytes) {
    asm volatile("mbarrier.arrive.expect_tx.relaxed.cluster.shared::cluster.b64 _, [%0], %1;" ::"r"(rbar), "r"(bytes) : "memory");
}
__device__ __forceinline__ void mbar_wait(uint32_t bar, uint32_t parity) {
    uint32_t done;
    for (;;) {
        asm volatile(
            "{\n\t.reg .pred p;\n\t"
            "mbarrier.try_wait.parity.shared::cta.b64 p, [%1], %2;\n\t"
            "selp.u32 %0, 1, 0, p;\n\t}"
            : "=r"(done) : "r"(bar), "r"(parity) : "memory");
        if (done) return;
    }
}
#define STAMP(t, j)
__device__ __forceinline__ uint32_t mbar_try(uint32_t bar, uint32_t parity) {
    uint32_t done;
    asm volatile("{\n\t.reg .pred p;\n\tmbarrier.try_wait.parity.shared::cta.b64 p, [%1], %2;\n\tselp.u32 %0, 1, 0, p;\n\t}"
                 : "=r"(done) : "r"(bar), "r"(parity) : "memory");
    return done;
}
#define HSL 0
__device__ __forceinline__ void mbar_wait_h(uint32_t bar, uint32_t parity) {
    mbar_wait(bar, parity);
}
__device__ __forceinline__ bool elect() {
    uint32_t el;
    asm volatile("{\n\t.reg .pred p;\n\telect.sync _|p, 0xffffffff;\n\tselp.u32 %0, 1, 0, p;\n\t}" : "=r"(el));
    return el;
}
__device__ __forceinline__ uint32_t mapa(uint32_t addr, uint32_t rank) {
    uint32_t r;
    asm("mapa.shared::cluster.u32 %0, %1, %2;" : "=r"(r) : "r"(addr), "r"(rank));
    return r;
}
__device__ __forceinline__ void tma_load_5d(uint32_t dst, const CUtensorMap* map, uint32_t bar,
                                            int c0, int c1, int c2, int c3, int c4, bool keep) {
    asm volatile(
        "cp.async.bulk.tensor.5d.shared::cluster.global.mbarrier::complete_tx::bytes "
        "[%0], [%1, {%3, %4, %5, %6, %7}], [%2];"
        ::"r"(dst), "l"((uint64_t)map), "r"(bar), "r"(c0), "r"(c1), "r"(c2), "r"(c3), "r"(c4) : "memory");
}
#define MRG 1
#define EFN 99
#define EFM 7
#define EFM2 0
#define EF(t, u) ((((t) < EFN ? EFM : EFM2) >> (u)) & 1)
__device__ __forceinline__ void tma_store_4d(const CUtensorMap* map, uint32_t src, int c0, int c1, int c2, int c3, bool ef) {
    uint64_t pol, pn;
    asm volatile("createpolicy.fractional.L2::evict_first.b64 %0, 1.0;" : "=l"(pol));
    asm volatile("createpolicy.fractional.L2::evict_normal.b64 %0, 1.0;" : "=l"(pn));
    if (!ef) pol = pn;
    asm volatile("cp.async.bulk.tensor.5d.global.shared::cta.bulk_group.L2::cache_hint [%0, {%2, %2, %3, %2, %4}], [%1], %5;"
                 ::"l"((uint64_t)map), "r"(src), "r"(c0), "r"(c3 * 128 + c1), "r"(c2), "l"(pol) : "memory");
}
__device__ __forceinline__ void load_row(uint32_t dst, uint32_t dstb, const CUtensorMap* xmap, uint32_t fb, int rank, int strip, int row, bool keep) {
    tma_load_5d(dst, xmap + 1, fb, rank * 64, 0, strip * 16 - 1, 0, row, keep);
    tma_load_5d(dstb, xmap, fb, 32 + rank * 16, 0, strip * 16 - 1, 0, row, keep);
}

__device__ __forceinline__ void wgmma_fence() { asm volatile("wgmma.fence.sync.aligned;" ::: "memory"); }
__device__ __forceinline__ void wgmma_commit() { asm volatile("wgmma.commit_group.sync.aligned;" ::: "memory"); }
template <int N>
__device__ __forceinline__ void wgmma_wait() { asm volatile("wgmma.wait_group.sync.aligned %0;" ::"n"(N) : "memory"); }

template <int SA>
__device__ __forceinline__ void wgmma_m64n96k16(float (&d)[48], const uint32_t* a, uint64_t db, int scale_d) {
    asm volatile(
        "{\n\t.reg .pred p;\n\t"
        "setp.ne.b32 p, %53, 0;\n\t"
        "wgmma.mma_async.sync.aligned.m64n96k16.f32.bf16.bf16 "
        "{%0, %1, %2, %3, %4, %5, %6, %7, %8, %9, %10, %11, %12, %13, %14, %15, "
        " %16, %17, %18, %19, %20, %21, %22, %23, %24, %25, %26, %27, %28, %29, %30, %31, "
        " %32, %33, %34, %35, %36, %37, %38, %39, %40, %41, %42, %43, %44, %45, %46, %47}, "
        "{%48, %49, %50, %51}, %52, p, %54, 1, 1;\n\t}"
        : "+f"(d[0]), "+f"(d[1]), "+f"(d[2]), "+f"(d[3]), "+f"(d[4]), "+f"(d[5]), "+f"(d[6]), "+f"(d[7]),
          "+f"(d[8]), "+f"(d[9]), "+f"(d[10]), "+f"(d[11]), "+f"(d[12]), "+f"(d[13]), "+f"(d[14]), "+f"(d[15]),
          "+f"(d[16]), "+f"(d[17]), "+f"(d[18]), "+f"(d[19]), "+f"(d[20]), "+f"(d[21]), "+f"(d[22]), "+f"(d[23]),
          "+f"(d[24]), "+f"(d[25]), "+f"(d[26]), "+f"(d[27]), "+f"(d[28]), "+f"(d[29]), "+f"(d[30]), "+f"(d[31]),
          "+f"(d[32]), "+f"(d[33]), "+f"(d[34]), "+f"(d[35]), "+f"(d[36]), "+f"(d[37]), "+f"(d[38]), "+f"(d[39]),
          "+f"(d[40]), "+f"(d[41]), "+f"(d[42]), "+f"(d[43]), "+f"(d[44]), "+f"(d[45]), "+f"(d[46]), "+f"(d[47])
        : "r"(a[0]), "r"(a[1]), "r"(a[2]), "r"(a[3]), "l"(db), "r"(scale_d), "n"(SA));
}

template <int N>
__device__ __forceinline__ void fence_regs(float (&r)[N]) {
#pragma unroll
    for (int i = 0; i < N; ++i) asm volatile("" : "+f"(r[i])::"memory");
}

__device__ __forceinline__ uint32_t bf2_add(uint32_t a, uint32_t b) {
    uint32_t r;
    asm volatile("add.rn.bf16x2 %0, %1, %2;" : "=r"(r) : "r"(a), "r"(b));
    return r;
}
__device__ __forceinline__ uint32_t bf2_sub(uint32_t a, uint32_t b) {
    uint32_t r;
    asm volatile("sub.rn.bf16x2 %0, %1, %2;" : "=r"(r) : "r"(a), "r"(b));
    return r;
}
template <uint32_t B>
__device__ __forceinline__ uint32_t bf2_fma(uint32_t a, uint32_t cc) {
    uint32_t r;
    asm volatile("fma.rn.bf16x2 %0, %1, %2, %3;" : "=r"(r) : "r"(a), "r"(B), "r"(cc));
    return r;
}
__device__ __forceinline__ uint32_t pack_bf16(float a, float b) {
    __nv_bfloat162 v = __floats2bfloat162_rn(a, b);
    return *reinterpret_cast<uint32_t*>(&v);
}

__device__ __forceinline__ uint32_t opaque_add(uint32_t a, uint32_t b) {
    uint32_t r;
    asm volatile("add.u32 %0, %1, %2;" : "=r"(r) : "r"(a), "r"(b));
    return r;
}
template <int K>
__device__ __forceinline__ void make_quads(uint32_t (&q)[12], const uint32_t (&x)[24], const uint32_t (&d2)[24],
                                           const uint32_t (&u)[24], int kc, uint32_t coef = 0) {
    uint32_t e[8];
#pragma unroll
    for (int i = 0; i < 8; ++i) e[i] = K == 1 ? bf2_add(x[kc * 8 + i], d2[kc * 8 + i]) : bf2_sub(x[kc * 8 + i], d2[kc * 8 + i]);
#pragma unroll
    for (int jj = 0; jj < 3; ++jj) {
        const int j = jj == 0 ? 1 : jj == 1 ? 0 : 2;
#pragma unroll
        for (int hl = 0; hl < 2; ++hl) {
#pragma unroll
            for (int h = 0; h < 2; ++h) {
                const int i = ((j + h) >> 1) * 4 + hl * 2 + ((j + h) & 1);
                const uint32_t uu = u[kc * 8 + i];
                if (K < 0) asm volatile("fma.rn.bf16x2 %0, %1, %2, %3;" : "=r"(q[j * 4 + hl * 2 + h]) : "r"(uu), "r"(coef), "r"(e[i]));
                else q[j * 4 + hl * 2 + h] = K == 0 ? bf2_fma<0x3f003f00u>(uu, e[i]) : K == 1 ? bf2_sub(e[i], uu)
                                      : K == 2 ? bf2_fma<0x40404040u>(e[i], uu) : bf2_fma<0xc000c000u>(uu, e[i]);
            }
        }
    }
}
template <bool MAKE_U, bool TIE>
__device__ __forceinline__ void make_mid(uint32_t (&q)[12], uint32_t (&d1)[24], const uint32_t (&d2)[24], uint32_t (&u)[24], int kc,
                                         const uint32_t (&d3)[24], uint32_t wg) {
    uint32_t y[8];
#pragma unroll
    for (int i = 0; i < 8; ++i) {
        y[i] = bf2_sub(d2[kc * 8 + i], d3[kc * 8 + i]);
        if (MAKE_U) asm volatile("sub.rn.bf16x2 %0, %0, %1;" : "+r"(u[kc * 8 + i]) : "r"(d1[kc * 8 + i]));
        if (TIE) asm volatile("{\n\t.reg .pred q;\n\tsetp.ne.u32 q, %3, 7;\n\t@q fma.rn.bf16x2 %0, %0, %2, %1;\n\t}" : "+r"(d1[kc * 8 + i]) : "r"(y[i]), "r"(0x40004000u), "r"(wg));
        else asm volatile("fma.rn.bf16x2 %0, %0, %2, %1;" : "+r"(d1[kc * 8 + i]) : "r"(y[i]), "r"(0x40004000u));
    }
#pragma unroll
    for (int jj = 0; jj < 3; ++jj) {
        const int j = jj == 0 ? 1 : jj == 1 ? 0 : 2;
#pragma unroll
        for (int hl = 0; hl < 2; ++hl) {
#pragma unroll
            for (int h = 0; h < 2; ++h) {
                const int i = ((j + h) >> 1) * 4 + hl * 2 + ((j + h) & 1);
                q[j * 4 + hl * 2 + h] = bf2_fma<0x3fc03fc0u>(y[i], u[kc * 8 + i]);
            }
        }
    }
}

struct Ctx {
    uint32_t bar;
    uint32_t wdesc;
    uint32_t wready, wg, tlo, k, zero, tlo2, vz, ua;
    int rk;
    uint32_t ld0, ld1;
    uint32_t xbuf;
    uint32_t r_off;
};

__device__ __forceinline__ void sb(const Ctx& c) {
    asm volatile("{\n\t.reg .pred q;\n\tsetp.eq.u32 q, %1, 7;\n\t@q mov.u32 %0, %clock;\n\t}" : "+r"(const_cast<Ctx&>(c).vz) : "r"(c.wg) : "memory");
}
__device__ __forceinline__ void sbz(const Ctx& c) {
    asm volatile("{\n\t.reg .pred q;\n\tsetp.eq.u32 q, %1, 7;\n\t@q mov.u32 %0, %clock;\n\t}" : "+r"(const_cast<Ctx&>(c).zero) : "r"(c.wg) : "memory");
}
#define FTW(n)
#define FTM
__device__ __forceinline__ void sbk(Ctx& c) {
    asm volatile("{\n\t.reg .pred q;\n\tsetp.eq.u32 q, %1, 7;\n\t@q mov.u32 %0, %clock;\n\t}" : "+r"(c.k) : "r"(c.wg) : "memory");
}
template <int OFF>
__device__ __forceinline__ void ldsm(uint32_t* r, uint32_t a, uint32_t ua) {
    asm volatile("{\n\t.reg .u32 t;\n\tadd.u32 t, %4, %5;\n\tldmatrix.sync.aligned.m8n8.x4.shared.b16 {%0, %1, %2, %3}, [t + %6];\n\t}"
                 : "=r"(r[0]), "=r"(r[1]), "=r"(r[2]), "=r"(r[3]) : "r"(a), "r"(ua), "n"(OFF) : "memory");
}
template <bool PLUS>
__device__ __forceinline__ uint32_t addr2(uint32_t b, uint32_t t) {
    uint32_t r;
    if (PLUS) asm volatile("mad.lo.s32 %0, %1, 2, %2;" : "=r"(r) : "r"(b), "r"(t));
    else asm volatile("{\n\t.reg .s32 x;\n\tneg.s32 x, %2;\n\tmad.lo.s32 %0, %1, 2, x;\n\t}" : "=r"(r) : "r"(b), "r"(t));
    return r;
}
template <int SLOT, int KC>
__device__ __forceinline__ void ld_chunk_t(uint32_t (&r)[24], const Ctx& c, uint32_t ua, uint32_t ub) {
    if (KC == 2) {
        ldsm<SLOT>(&r[16], c.ld0, ub);
        ldsm<SLOT>(&r[20], c.ld1, ub);
    } else {
        ldsm<2 * SLOT + KC * 16>(&r[KC * 8], addr2<KC == 0>(c.ld0, c.vz), ua);
        ldsm<2 * SLOT + 16 - KC * 16>(&r[KC * 8 + 4], addr2<KC != 0>(c.ld1, c.vz), ua);
    }
}
#define ld_chunk(r, c, slot, kc) ld_chunk_t<slot, kc>(r, c, c.ua, 0)

__device__ __forceinline__ void mma3p(float (&acc)[48], const uint32_t* q0, const uint32_t* q1, const uint32_t* q2,
                                      const Ctx& c, int k, int kc, bool fresh) {
    uint32_t wd;
    asm volatile("mov.b32 %0, %1;" : "=r"(wd) : "r"(c.wdesc));
    wgmma_fence();
#pragma unroll
    for (int j = 0; j < 3; ++j) {
        const uint32_t lo = wd + (uint32_t)((CP(k) * W_COMP + j * W_TAP + (kc == 2 ? 4 - 4 * c.rk : kc + 2 * c.rk) * W_K8) >> 4);
        const uint32_t hi = (uint32_t)((kc == 2 ? W_K8 : 2 * W_K8) >> 4) | (2u << 30);
        uint64_t db;
        asm("mov.b64 %0, {%1, %2};" : "=l"(db) : "r"(lo), "r"(hi));
        if (k == 3 && c.rk == 1) wgmma_m64n96k16<-1>(acc, j == 0 ? q0 : j == 1 ? q1 : q2, db, (fresh && j == 0) ? 0 : 1);
        else wgmma_m64n96k16<1>(acc, j == 0 ? q0 : j == 1 ? q1 : q2, db, (fresh && j == 0) ? 0 : 1);
    }
    wgmma_commit();
}
__device__ __forceinline__ void mma3(float (&acc)[48], const uint32_t (&q)[12], const Ctx& c, int k, int kc, bool fresh) {
    mma3p(acc, &q[0], &q[4], &q[8], c, k, kc, fresh);
}
__device__ __forceinline__ void make_dup(uint32_t (&q)[12], const uint32_t (&u)[24], const Ctx& c, int kc) {
#pragma unroll
    for (int i = 0; i < 4; ++i)
        q[kc * 4 + i] = opaque_add(u[kc * 8 + (i & 1) * 3 + (i >> 1) * 2 + 1], c.zero);
}
__device__ __forceinline__ void mma3d(float (&acc)[48], const uint32_t (&u)[24], const uint32_t (&q)[12], const Ctx& c, int k, int kc, int first = 0) {
    mma3p(acc, &u[kc * 8], &q[kc * 4], &u[kc * 8 + 4], c, k, kc, kc == first);
}
__device__ __forceinline__ void mma3u(float (&acc)[48], const uint32_t (&u)[24], uint32_t (&q)[12], const Ctx& c, int kc) {
    make_dup(q, u, c, kc);
    mma3d(acc, u, q, c, 3, kc);
}

__device__ __forceinline__ uint32_t pack_word(const float (&acc)[48], int i, int m) {
    const int o = ((i % 3) * 4 + m) * 4 + (i / 3) * 2;
    return pack_bf16(acc[o], acc[o + 1]);
}
__device__ __forceinline__ void st_async(uint32_t addr, uint32_t r0, uint32_t r1, uint32_t r2, uint32_t r3, uint32_t rbar) {
    asm volatile("st.async.weak.shared::cluster.mbarrier::complete_tx::bytes.v4.b32 [%0], {%1, %2, %3, %4}, [%5];"
                 ::"r"(addr), "r"(r0), "r"(r1), "r"(r2), "r"(r3), "r"(rbar) : "memory");
}
template <int I>
__device__ __forceinline__ void send_acc(float (&acc)[48], uint32_t (&kp)[24], const Ctx& c, int n, int at, int spk) {
    if (n == (at < spk ? at : spk)) {
        fence_regs(acc);
#pragma unroll
        for (int m = 0; m < 4; ++m) {
            if (at > spk) asm volatile("add.rn.bf16x2 %0, %0, %1;" : "+r"(kp[I * 4 + m]) : "r"(pack_word(acc, I, m)));
            else kp[I * 4 + m] = GAPB == 2 ? bf2_add(pack_word(acc, I, m), kp[I * 4 + m]) : pack_word(acc, I, m);
        }
    }
    if (n != at) return;
    const uint32_t ro = c.r_off + (c.zero >> n), rx = c.xbuf + ro, rb = c.bar + B_FFULL + ro;
    st_async(rx + (I / 3) * X_UNIT + (I % 3) * X_CH, kp[I * 4], kp[I * 4 + 1], kp[I * 4 + 2], kp[I * 4 + 3], rb);
}
template <int I, bool H = true, int BH = B_HFULL>
__device__ __forceinline__ void send_half(const uint32_t (&p)[12], const Ctx& c, int n = 0) {
    const uint32_t ro = c.r_off + (c.zero >> n), rx = c.xbuf + ro, rb = c.bar + (H ? BH : B_FFULL) + ro;
    st_async(rx + (H ? 2 * X_UNIT : 0) + I * X_CH, p[I * 4], p[I * 4 + 1], p[I * 4 + 2], p[I * 4 + 3], rb);
}
template <int I0, int N>
__device__ __forceinline__ void fin_pack(float (&acc)[48], uint32_t (&pk)[N * 4]) {
    fence_regs(acc);
#pragma unroll
    for (int i = 0; i < N * 4; ++i) {
        pk[i] = pack_word(acc, I0 + (i >> 2), i & 3);
        asm volatile("" : "+r"(pk[i]));
    }
}
template <int N>
__device__ __forceinline__ void fin_load(uint32_t (&v)[N * 4], const Ctx& c, int off) {
#pragma unroll
    for (int i = 0; i < N; ++i)
        asm volatile("ld.shared.v4.b32 {%0, %1, %2, %3}, [%4];"
                     : "=r"(v[i * 4 + 0]), "=r"(v[i * 4 + 1]), "=r"(v[i * 4 + 2]), "=r"(v[i * 4 + 3])
                     : "r"(c.xbuf + off + (i / 3) * X_UNIT + (i % 3) * X_CH) : "memory");
}
template <int N>
__device__ __forceinline__ void fin_store(uint32_t (&pk)[N * 4], const uint32_t (&v)[N * 4], const Ctx& c, int off, int sbar) {
#pragma unroll
    for (int i = 0; i < N; ++i) {
#pragma unroll
        for (int j = i * 4; j < i * 4 + 4; ++j) asm volatile("add.rn.bf16x2 %0, %0, %1;" : "+r"(pk[j]) : "r"(v[j]));
        asm volatile("st.shared.v4.b32 [%0], {%1, %2, %3, %4};"
                     ::"r"(c.xbuf + off + (i / 3) * X_UNIT + (i % 3) * X_CH), "r"(pk[i * 4]), "r"(pk[i * 4 + 1]), "r"(pk[i * 4 + 2]),
                       "r"(pk[i * 4 + 3]) : "memory");
    }
    if (sbar >= 0) mbar_arrive_warp(c.bar + sbar);
}

__device__ __forceinline__ void pin(const uint32_t* r, const Ctx& c) {
    asm volatile("{\n\t.reg .pred q;\n\tsetp.ne.u32 q, %12, 7;\n\t@q bra.uni PIN_SKIP;\n\t"
                 "st.volatile.shared.v4.b32 [%13], {%0, %1, %2, %3};\n\tst.volatile.shared.v4.b32 [%13], {%4, %5, %6, %7};\n\t"
                 "st.volatile.shared.v4.b32 [%13], {%8, %9, %10, %11};\n\tPIN_SKIP:\n\t}"
                 ::"r"(r[0]), "r"(r[1]), "r"(r[2]), "r"(r[3]), "r"(r[4]), "r"(r[5]), "r"(r[6]), "r"(r[7]), "r"(r[8]), "r"(r[9]),
                   "r"(r[10]), "r"(r[11]), "r"(c.wg), "r"(c.bar) : "memory");
}
__device__ __forceinline__ void pin4(const uint32_t* r, const Ctx& c) {
    asm volatile("{\n\t.reg .pred q;\n\tsetp.eq.u32 q, %4, 7;\n\t@q st.volatile.shared.v4.b32 [%5], {%0, %1, %2, %3};\n\t}"
                 ::"r"(r[0]), "r"(r[1]), "r"(r[2]), "r"(r[3]), "r"(c.wg), "r"(c.bar) : "memory");
}
__device__ __forceinline__ void acc_add(float& d, float x, float k) {
    asm volatile("fma.rn.f32 %0, %1, %2, %0;" : "+f"(d) : "f"(x), "f"(k));
}
__device__ __forceinline__ void acc_scale_add(float& d, float k, float x) {
    asm volatile("fma.rn.f32 %0, %0, %2, %1;" : "+f"(d) : "f"(x), "f"(k));
}
template <int RANK, int I0 = 0, int I1 = 24>
__device__ __forceinline__ void mid_row(float (&b)[48], const float (&k)[48], uint32_t (&ps)[12], uint32_t (&pk)[12],
                                        float f = -2.f) {
#pragma unroll
    for (int i = I0; i < I1; ++i) {
        const int ch = i >> 2, o = ((ch % 3) * 4 + (i & 3)) * 4 + (ch / 3) * 2;
        acc_scale_add(b[o], f, k[o]);
        acc_scale_add(b[o + 1], f, k[o + 1]);
        uint32_t& dst = (i / 12 == RANK) ? pk[i % 12] : ps[i % 12];
        dst = pack_bf16(b[o], b[o + 1]);
        asm volatile("" : "+r"(dst));
    }
}
template <int RANK>
__device__ __forceinline__ void mid_row2(float (&b)[48], const float (&k)[48], uint32_t (&ps)[12], uint32_t (&pk)[12], uint32_t (&kp)[24]) {
#pragma unroll
    for (int j = 0; j < 24; ++j) {
        const int i = EPK & 16 ? (j >> 1) + 12 * (j & 1) : (j + 12 - 12 * RANK) % 24;
        const int ch = i >> 2, o = ((ch % 3) * 4 + (i & 3)) * 4 + (ch / 3) * 2;
        const bool keep = i / 12 == RANK;
        uint32_t& dst = keep ? pk[i % 12] : ps[i % 12];
        if (!((PKH >> (keep ? 0 : 1)) & 1)) {
            acc_scale_add(b[o], -2.f, k[o]);
            acc_scale_add(b[o + 1], -2.f, k[o + 1]);
        }
        if (!((PKH & EPK) >> (keep ? 0 : 1) & 1)) dst = pack_bf16(b[o], b[o + 1]);
        if (!keep && (PKH & 2)) {
            kp[i] = pack_bf16(k[o], k[o + 1]);
            asm volatile("" : "+r"(kp[i]));
            dst = bf2_fma<0xc000c000u>(dst, kp[i]);
        }
        asm volatile("" : "+r"(dst));
    }
}
template <int RANK>
__device__ __forceinline__ void pack_k(const float (&k)[48], uint32_t (&kp)[24]) {
#pragma unroll
    for (int i = 0; i < 24; ++i) {
        if (i / 12 != RANK && (PKH & 2)) continue;
        kp[i] = pack_word(k, i >> 2, i & 3);
        asm volatile("" : "+r"(kp[i]));
    }
}
template <int RANK>
__device__ __forceinline__ void fix_hk(uint32_t (&hk)[12], const uint32_t (&kp)[24]) {
    if (PKH & 1) {
#pragma unroll
        for (int i = 0; i < 12; ++i) asm volatile("fma.rn.bf16x2 %0, %0, %2, %1;" : "+r"(hk[i]) : "r"(kp[RANK * 12 + i]), "r"(0xc000c000u));
    }
}
template <int I0, int I1>
__device__ __forceinline__ void acc_add_n(float (&d)[48], const float (&x)[48], float k) {
#pragma unroll
    for (int i = I0; i < I1; ++i) acc_add(d[i], x[i], k);
}

template <int RANK, bool LAST, int I0, int I1>
__device__ __forceinline__ void acc_add_pk(float (&d)[48], const float (&x)[48], float k, uint32_t (&ps)[12], uint32_t (&pk)[12]) {
    if (LAST || !(EPK & 3)) { acc_add_n<I0, I1>(d, x, k); return; }
#pragma unroll
    for (int j = I0 / 2; j < I1 / 2; ++j) {
        const int i = EPK & 8 ? (j >> 1) + 12 * (j & 1) : (j + 12 * ((EPK >> 2 ^ RANK) & 1)) % 24;
        const int ch = i >> 2, o = ((ch % 3) * 4 + (i & 3)) * 4 + (ch / 3) * 2;
        const bool keep = i / 12 == RANK;
        uint32_t& dst = keep ? pk[i % 12] : ps[i % 12];
        acc_add(d[o], x[o], k);
        acc_add(d[o + 1], x[o + 1], k);
        if ((PKH & EPK) >> (keep ? 0 : 1) & 1) {
            dst = pack_bf16(d[o], d[o + 1]);
            asm volatile("" : "+r"(dst));
        }
    }
}

#define LOCK 1
__device__ __forceinline__ void stagger_lead(const Ctx& c, uint32_t id) {
    if (LOCK) {
        asm volatile("{\n\t.reg .pred p;\n\tsetp.eq.u32 p, %1, 0;\n\t@p bar.sync %0, 256;\n\t}" ::"r"(id), "r"(c.wg) : "memory");
        return;
    }
    asm volatile("{\n\t.reg .pred p;\n\tsetp.eq.u32 p, %1, 0;\n\t@p bar.arrive %0, 256;\n\t}" ::"r"(id), "r"(c.wg) : "memory");
}
__device__ __forceinline__ void stagger_lag(const Ctx& c, uint32_t id) {
    asm volatile("{\n\t.reg .pred p;\n\tsetp.ne.u32 p, %1, 0;\n\t@p bar.sync %0, 256;\n\t}" ::"r"(id), "r"(c.wg) : "memory");
}

template <int ID, int WG, bool ARR = false>
__device__ __forceinline__ void lock(const Ctx& c) {
    if (ARR) asm volatile("{\n\t.reg .pred p;\n\tsetp.eq.u32 p, %0, %1;\n\t@p bar.arrive %2, 256;\n\t}" ::"r"(c.wg), "n"(WG), "n"(ID) : "memory");
    else if (WG == 0) asm volatile("{\n\t.reg .pred p;\n\tsetp.eq.u32 p, %0, 0;\n\t@p bar.sync %1, 256;\n\t}" ::"r"(c.wg), "n"(ID) : "memory");
    else asm volatile("{\n\t.reg .pred p;\n\tsetp.ne.u32 p, %0, 0;\n\t@p bar.sync %1, 256;\n\t}" ::"r"(c.wg), "n"(ID) : "memory");
}
#define LA0 1319
#define LB0 9999
#define LC0 9999
#define LA1 LA0
#define LB1 LB0
#define LC1 LC0
#define LA (RANK == 0 ? LA0 : LA1)
#define LB (RANK == 0 ? LB0 : LB1)
#define LC (RANK == 0 ? LC0 : LC1)
#define LORD(p) ((p) >= 24 ? (p) - 24 : (p) + 8)
#define LWRAP(L) (LORD((L) % 100) < LORD((L) / 100))
#define LK(p)                                                                        \
    do {                                                                             \
        if (LA / 100 == (p)) lock<1, 1>(c);                                          \
        if (LB / 100 == (p)) lock<2, 1>(c);                                          \
        if (LC / 100 == (p)) lock<3, 1>(c);                                          \
        if (LA % 100 == (p)) lock<1, 0>(c);                                          \
        if (LB % 100 == (p)) lock<2, 0>(c);                                          \
        if (LC % 100 == (p)) lock<3, 0>(c);                                          \
    } while (0)
#define DEFM 0
#define M1O 0x012
#define M1O0 M1O
#define MO(i) (((RANK == 0 ? M1O0 : M1O) >> (8 - 4 * (i))) & 3)
#define QHW 1
#define CPY 0
#define LDP 0
#define DUPL 0
#define PQ0 0
#define PQ1 0
#define TIE0 0
#define TIE1 0
#define WA 0
#define WB 0
#define PKF (AT(23) == PKSLOT)
#define PROBE 0
#define PAPOS 0
#define PPOS 1
#define CS1 16
#define EPI 0
#define WTOP 1
#define FT_BASE 538
#define SBA 0x8000ull
#define SBB 0x20ull
template <int N>
__device__ __forceinline__ void sbx(const Ctx& c) {
    if (!(((N < 64 ? SBA : SBB) >> (N & 63)) & 1)) sb(c);
}
#define sb(c) sbx<__COUNTER__>(c)
template <int RANK, bool LAST>
__device__ __forceinline__ void phase1b(Ctx& c, float (&accS)[48], float (&accK)[48], float (&accC)[48],
                                        uint32_t (&d0)[24], uint32_t (&d1)[24], const uint32_t (&d2)[24],
                                        const uint32_t (&u)[24], uint32_t (&qd)[12], uint32_t (&qh)[12],
                                        uint32_t (&hs)[12], uint32_t (&hk)[12]) {
    uint32_t pa_ = 0;
    if ((PROBE & 1) && PAPOS == 0) pa_ = mbar_try(c.bar + B_FULLA, LAST ? (NIT - 1) & 1 : c.k & 1);
    if (WTOP == 1) wgmma_wait<0>();
    fence_regs(accS);
    fence_regs(accC);
#pragma unroll
    for (int i = 0; i < 48; ++i)
        asm volatile("fma.rn.f32 %0, %1, %2, %3;" : "=f"(accK[i]) : "f"(accS[i]), "f"(RANK == 0 ? 1.f / 3.f : -4.f / 3.f), "f"(accC[i]));
    constexpr float CF = RANK == 0 ? -1.f / 6.f : -1.f / 3.f;
    if (DUPL) make_dup(qd, d1, c, MO(0));
    mma3d(accK, d1, qd, c, 1, MO(0), -1);
    sb(c);
    if ((PROBE & 1) && PAPOS == 1) pa_ = mbar_try(c.bar + B_FULLA, LAST ? (NIT - 1) & 1 : c.k & 1);
    if (!LAST) LK(24);
    make_dup(qd, d1, c, MO(1));
    mma3d(accK, d1, qd, c, 1, MO(1), -1);
    sb(c);
    if ((PROBE & 1) && PAPOS == 2) pa_ = mbar_try(c.bar + B_FULLA, LAST ? (NIT - 1) & 1 : c.k & 1);
    if (!LAST) LK(26);
    acc_add_pk<RANK, LAST, 0, CS1>(accC, accS, CF, hs, hk);
    if (PROBE & 16) sb(c);
    if (__builtin_expect(!pa_, PROBE & 1 ? 0 : 1)) mbar_wait(c.bar + B_FULLA, LAST ? (NIT - 1) & 1 : c.k & 1);
    if (WA == 1 && !LAST && c.k == 0) mbar_wait(c.bar + B_FULLA, 0);
    if (WA) sb(c);
    wgmma_wait<1>();
    if (LDP == 1) sb(c);
    if (LDP < 2) {
        if (RANK == 0 && !LAST) ld_chunk(d1, c, SL4, 0);
        else ld_chunk(d0, c, SL0, 0);
    }
    make_dup(qd, d1, c, MO(2));
    mma3d(accK, d1, qd, c, 1, MO(2), -1);
    sb(c);
    if (!LAST) LK(28);
    if (LDP == 2) {
        if (RANK == 0 && !LAST) ld_chunk(d1, c, SL4, 0);
        else ld_chunk(d0, c, SL0, 0);
    }
    if (LAST && (EPI & 2)) ld_chunk(d0, c, SL0, 1);
    acc_add_pk<RANK, LAST, CS1, 48>(accC, accS, CF, hs, hk);
    sb(c);
    wgmma_wait<QHW>();
    if (LDP == 3) {
        if (RANK == 0 && !LAST) ld_chunk(d1, c, SL4, 0);
        else ld_chunk(d0, c, SL0, 0);
    }
    if (LAST && (EPI & 1) && !(EPI & 2)) ld_chunk(d0, c, SL0, 1);
    if (LAST && (EPI & 1)) { ld_chunk(d0, c, SL0, 2); sb(c); }
    if (RANK == 0 && !LAST) make_quads<4>(qh, d1, d2, u, 0);
    else make_quads<0>(qh, d0, d2, u, 0);
    sb(c);
}

#define WFA 1
#define P1MC 1
#define P2MC 6
#define WF1C 0
template <int RANK>
__device__ __forceinline__ void consumer(Ctx& c) {
    float accS[48], accK[48], accC[48];
    uint32_t d0[24], d1[24], d2[24], u[24];
    uint32_t qd[12];
#pragma unroll
    for (int i = 0; i < 48; ++i) { accS[i] = 0.f; accC[i] = 0.f; }
    {
        uint32_t qa[12], qe[12];
#define PRO 126
        if ((PRO & 1) || ((PRO & 32) && c.wg)) {
            mbar_wait(c.wready, 0);
            if (!WF1C) asm volatile("fence.proxy.async.shared::cta;" ::: "memory");
            TL(18);
        }
        mbar_wait(c.bar + B_FULL0, 0);
        c.rk = RANK;
        sbz(c);
        const uint32_t xo = (uint32_t)(OFF_X - OFF_IN) - c.wg * (4 * IN_ROW - X_BYTES);
        uint32_t (&d3)[24] = PRO & 4 ? d0 : u;
        ld_chunk_t<0, 0>(d1, c, c.ua + xo, 0);
        ld_chunk(d3, c, SL3, 0);
#define PLD 1
        if (PLD < 2) {
            ld_chunk_t<0, 1>(d1, c, c.ua + xo, 0);
            ld_chunk(d3, c, SL3, 1);
        }
        if (PLD < 1) {
            ld_chunk_t<0, 2>(d1, c, 0, xo + 2 * IN_SLAB - IN_B);
            ld_chunk(d3, c, SL3, 2);
        }
        if (PRO & 2) {
#pragma unroll
            for (int kc = 0; kc < 3; ++kc) {
                if (kc == 1 && PLD == 2) {
                    ld_chunk_t<0, 1>(d1, c, c.ua + xo, 0);
                    ld_chunk(d3, c, SL3, 1);
                }
                if (kc == 1 && PLD) {
                    ld_chunk_t<0, 2>(d1, c, 0, xo + 2 * IN_SLAB - IN_B);
                    ld_chunk(d3, c, SL3, 2);
                }
                if (kc == 2 && (PRO & 64)) {
                    mbar_wait(c.bar + B_FULLC, 0);
                    ld_chunk(d2, c, SL2, 0);
                }
#pragma unroll
                for (int i = kc * 8; i < kc * 8 + 8; ++i) u[i] = bf2_sub(d3[i], d1[i]);
                make_dup(qe, u, c, kc);
                if (kc == 0 && (PRO & 32) && !c.wg) {
                    TL(18);
                    mbar_wait(c.wready, 0);
                    asm volatile("fence.proxy.async.shared::cta;" ::: "memory");
                }
                if (kc == 0) TL(19);
                mma3d(accS, u, qe, c, 3, kc);
                sb(c);
            }
        } else {
#pragma unroll
            for (int i = 0; i < 24; ++i) u[i] = bf2_sub(d3[i], d1[i]);
#pragma unroll
            for (int kc = 0; kc < 3; ++kc) make_dup(qe, u, c, kc);
            if (!(PRO & 1)) {
                TL(18);
                mbar_wait(c.wready, 0);
                if (!WF1C) asm volatile("fence.proxy.async.shared::cta;" ::: "memory");
            }
            TL(19);
#pragma unroll
            for (int kc = 0; kc < 3; ++kc) mma3d(accS, u, qe, c, 3, kc);
        }
        if (!(PRO & 64)) mbar_wait(c.bar + B_FULLC, 0);
        if (!(P1MC & 2) && !(PRO & 8)) mbar_wait(c.wready + (P2MC ? 32 : 16), 0);
        if (!(PRO & 64)) ld_chunk(d2, c, SL2, 0);
        if (!(PRO & 4)) ld_chunk(d0, c, SL3, 0);
        ld_chunk(d2, c, SL2, 1);
        if (!(PRO & 4)) ld_chunk(d0, c, SL3, 1);
        else ld_chunk(d2, c, SL2, 2);
        if (!(P1MC & 2) && (PRO & 8)) mbar_wait(c.wready + (P2MC ? 32 : 16), 0);
#pragma unroll
        for (int kc = 0; kc < 3; ++kc) {
            if (kc == 1 && !(PRO & 4)) { sb(c); ld_chunk(d2, c, SL2, 2); ld_chunk(d0, c, SL3, 2); }
#pragma unroll
            for (int i = kc * 8; i < kc * 8 + 8; ++i) {
                asm volatile("sub.rn.bf16x2 %0, %1, %0;" : "+r"(d0[i]) : "r"(d2[i]));
                asm volatile("fma.rn.bf16x2 %0, %0, %2, %1;" : "+r"(d1[i]) : "r"(d0[i]), "r"(0x40004000u));
                asm volatile("fma.rn.bf16x2 %0, %0, %2, %1;" : "+r"(d0[i]) : "r"(u[i]), "r"(0x3fc03fc0u));
            }
            make_dup(qa, d0, c, kc);
            mma3d(accC, d0, qa, c, 2, kc);
            if (PRO & 16) sb(c);
        }
        mbar_arrive_warp(c.bar + B_EMPTYB);
        if (!DUPL) make_dup(qd, d1, c, MO(0));
        if (LWRAP(LA)) lock<1, 1>(c);
        if (LWRAP(LB)) lock<2, 1>(c);
        if (LWRAP(LC)) lock<3, 1>(c);
        if (WA == 2) mbar_wait(c.bar + B_FULLA, 0);
        if ((P2MC || (P1MC & 2)) && !WFA) mbar_wait(c.wready + 16, 0);
        wgmma_wait<0>();
        c.k = c.zero;
        TL(23);
    }
    constexpr int KA = RANK == 0 ? 4 : 0, KB = 4 - KA;
    constexpr int SA = RANK == 0 ? SL4 : SL0, SB = RANK == 0 ? SL0 : SL4;
    uint32_t (&ea)[24] = RANK == 0 ? d1 : d0;
    uint32_t (&eb)[24] = RANK == 0 ? d0 : d1;
#pragma unroll 1
    while (c.k < NIT - 1) {
#define par(n) ((c.k + (c.zero >> n)) & 1)
        uint32_t qa[12], qb[12], qe[12], qh[12], hs[12], hk[12];
        uint32_t hv[12], pa[12], pb[12], va[12], vb[12], kp[24], pb_ = 0, ph_ = 0, pf_ = 0;
        phase1b<RANK, false>(c, accS, accK, accC, d0, d1, d2, u, qd, qh, hs, hk);
#define AT(i) (int)(((RANK == 0 ? (i < 16 ? PLA0 : PLB0) : (i < 16 ? PLA1 : PLB1)) >> (60 - 4 * (i & 15))) & 15)
#define SLOT(n)                                                                                   \
        if (n < 12) { LK(2 * (n)); }                                                              \
        if (AT(2) == n && FMODE != 1) mbar_wait(c.bar + B_FULL0 + FMODE * 8, par(n));             \
        if (PPOS == 0) { PROBES(n) } if (AT(5) == n && __builtin_expect(!pb_, PROBE & 2 ? 0 : 1)) mbar_wait(c.bar + B_FULLB, par(n));                         \
        if (!(MRG & 1) && AT(14) == n && __builtin_expect(!ph_, PROBE & 4 ? 0 : 1)) mbar_wait(c.bar + B_HFULL, par(n));                                      \
        if (AT(22) == n && __builtin_expect(!pf_, PROBE & 8 ? 0 : 1)) mbar_wait(c.bar + B_FFULL, par(n));                                      \
        if (n == 2) mbar_arrive_warp(c.bar + B_EMPTYE);                                           \
        if (n == 5 && !(MRG & 2)) mbar_arrive_warp(c.bar + B_EMPTYF);                                           \
        if (n == EBSLOT) mbar_arrive_warp(c.bar + B_EMPTYB);                                      \
        if (!LLATE(n)) { LOADS(n) }                                                               \
        if (!LATE(n)) { STORES(n) }                                                               \
        if (PPOS == 1) { PROBES(n) }
#define PROBES(n)                                                                                 \
        if ((PROBE & 2) && AT(5) == n + 1) pb_ = mbar_try(c.bar + B_FULLB, par(n));              \
        if ((PROBE & 4) && AT(14) == n + 1) ph_ = mbar_try(c.bar + B_HFULL, par(n));              \
        if ((PROBE & 8) && AT(22) == n + 1) pf_ = mbar_try(c.bar + B_FFULL, par(n));
#define LOADS(n)                                                                                  \
        if (AT(0) == n) ld_chunk(ea, c, SA, 1);                                                   \
        if (AT(1) == n) ld_chunk(ea, c, SA, 2);                                                   \
        if (AT(2) == n) ld_chunk(eb, c, SB, 0);                                                   \
        if (AT(3) == n) ld_chunk(eb, c, SB, 1);                                                   \
        if (AT(4) == n) ld_chunk(eb, c, SB, 2);                                                   \
        if (AT(5) == n) ld_chunk(u, c, SL3, 0);                                                   \
        if (AT(6) == n) ld_chunk(d2, c, SL2, 0);                                                  \
        if (AT(7) == n) ld_chunk(u, c, SL3, 1);                                                   \
        if (AT(8) == n) ld_chunk(d2, c, SL2, 1);                                                  \
        if (AT(9) == n) ld_chunk(u, c, SL3, 2);                                                   \
        if (AT(10) == n) ld_chunk(d2, c, SL2, 2);                                                 \
        if (AT(14) == n) fin_load<3>(hv, c, 2 * X_UNIT);                                          \
        if (AT(22) == n) fin_load<3>(va, c, 0);                                                   \
        if (AT(24) == n) fin_load<3>(vb, c, X_UNIT);
#define STORES(n)                                                                                 \
        if (n == PKSLOT && PKF) { fin_pack<0, 3>(accK, pa); fin_pack<3, 3>(accK, pb); if (AT(23) != n) pin(pa, c); if (AT(25) != n) pin(pb, c); } \
        if (AT(15) == n) fin_store<3>(hk, hv, c, 2 * X_UNIT, B_SH);                               \
        if (AT(23) == n) fin_store<3>(pa, va, c, 0, -1);                                          \
        if (AT(25) == n) fin_store<3>(pb, vb, c, X_UNIT, B_SF);                                   \
        if (LLATE(n) && !LLATE2(n)) { LOADS(n) }                                                  \
        if (AT(11) == n) send_half<0, true, (MRG & 1) ? B_FULLB : B_HFULL>(hs, c, n);                                                  \
        if (AT(12) == n) send_half<1, true, (MRG & 1) ? B_FULLB : B_HFULL>(hs, c, n);                                                  \
        if (AT(13) == n) send_half<2, true, (MRG & 1) ? B_FULLB : B_HFULL>(hs, c, n);                                                  \
        send_acc<0>(accS, kp, c, n, AT(16), SPK);                                          \
        send_acc<3>(accS, kp, c, n, AT(17), SPK);                                          \
        send_acc<1>(accS, kp, c, n, AT(18), SPK);                                          \
        send_acc<4>(accS, kp, c, n, AT(19), SPK);                                          \
        send_acc<2>(accS, kp, c, n, AT(20), SPK);                                          \
        send_acc<5>(accS, kp, c, n, AT(21), SPK);                                          \
        if (LLATE(n) && LLATE2(n)) { LOADS(n) }                                                   \
        if (n == PKSLOT && !PKF) { fin_pack<0, 3>(accK, pa); fin_pack<3, 3>(accK, pb); pin(pa, c); pin(pb, c); }
#define QW(n, Q)                                                                     \
        if (LATE(n)) { Q; sb(c); STORES(n); sb(c); wgmma_wait<1 + NW(n)>(); FTW(n); }        \
        else if (EQ(n)) { Q; sb(c); wgmma_wait<1 + NW(n)>(); FTW(n); } else { sb(c); wgmma_wait<1 + NW(n)>(); FTW(n); Q; } \
        if (PPOS == 2) { PROBES(n) }                                                              \
        LK(2 * (n) + 1);
#define P1(g, q)                                                                                  \
        SLOT(g + 5);                                                                              \
        if (PG(g) < 4) {                                                                          \
            QW(g + 5, (make_mid<true, (((RANK == 0 ? TIE0 : TIE1) >> (PG(g) & 3)) & 1) != 0>(q, d1, d2, u, PG(g) & 3, u, c.wg)));                                 \
            mma3(accC, q, c, 2, PG(g) & 3, g == 0);                                               \
        } else {                                                                                  \
            QW(g + 5, make_dup(qe, u, c, PG(g) & 3));                                             \
            mma3d(accS, u, qe, c, 3, PG(g) & 3, M1FIRST);                                         \
        }
        if (!GAPB) {
            wgmma_wait<0>();
            fence_regs(accK);
            if (!DEFM) {
                mid_row<RANK>(accC, accK, hs, hk);
                pin(hk, c);
                SLOT(15);
            } else {
                LOADS(15);
            }
            sbk(c);
            acc_add_n<0, 48>(accS, accK, 1.f);
            mma3(accS, qh, c, KA, 0, false);
            sb(c);
            if (DEFM) {
                mid_row<RANK>(accC, accK, hs, hk);
                pin(hk, c);
                STORES(15);
                sb(c);
            }
        } else {
            mma3(accS, qh, c, KA, 0, false);
            LK(30);
            wgmma_wait<1>();
            LK(31);
            fence_regs(accK);
            LOADS(15);
            sbk(c);
            if (GAPB == 2) mid_row2<RANK>(accC, accK, hs, hk, kp);
            else mid_row<RANK>(accC, accK, hs, hk);
            pin(hk, c);
            STORES(15);
            sb(c);
        }
#define PK_(n, e) if (GAPB == 2 && KPS == n && KPE == e) pack_k<RANK>(accK, kp); if (GAPB == 2 && HKS == n && KPE == e) fix_hk<RANK>(hk, kp);
        PK_(0, 2)
        SLOT(0);
        PK_(0, 1)
        make_quads<KA>(qa, ea, d2, u, 1);
        PK_(0, 0)
        LK(1);
        mma3(accS, qa, c, KA, 1, false);
        sb(c);
        PK_(1, 2)
        SLOT(1);
        PK_(1, 1)
        QW(1, make_quads<KA>(qb, ea, d2, u, 2); PK_(1, 0));
        mma3(accS, qb, c, KA, 2, false);
        sb(c);
        PK_(2, 2)
        SLOT(2);
        PK_(2, 1)
        QW(2, make_quads<KB>(qa, eb, d2, u, 0); PK_(2, 0));
        if (WB) mbar_wait(c.bar + B_FULLB, par(2));
        if (WB == 2) mbar_wait(c.bar + B_HFULL, par(2));
        if (GAPB == 1) {
            wgmma_wait<0>();
            fence_regs(accS);
            acc_add_n<0, 48>(accS, accK, 1.f);
        }
        mma3(accK, qa, c, KB, 0, false);
        sb(c);
        PK_(3, 2)
        SLOT(3);
        PK_(3, 1)
        QW(3, make_quads<KB>(qb, eb, d2, u, 1); PK_(3, 0));
        mma3(accK, qb, c, KB, 1, false);
        sb(c);
        PK_(4, 2)
        SLOT(4);
        QW(4, make_quads<KB>(qa, eb, d2, u, 2));
        mma3(accK, qa, c, KB, 2, false);
        sb(c);
        P1(0, qb);

        sb(c);
        P1(1, qa);

        sb(c);
        P1(2, qb);

        sb(c);
        P1(3, qa);

        sb(c);
        P1(4, qb);

        sb(c);
        P1(5, qa);

        sb(c);
        SLOT(11);
        LK(23);
        if (!DUPL) make_dup(qd, d1, c, MO(0));
#pragma unroll
        for (int i = 0; i < 12; ++i)
            if (((RANK == 0 ? PQ0 : PQ1) >> i) & 1) pin4(&d2[(i % 6) * 4], c);
        sbz(c);
        ++c.k;
        if (WA) mbar_wait(c.bar + B_FULLA, c.k & 1);
        if (WTOP == 2) asm volatile("{\n\t.reg .pred q;\n\tsetp.ge.u32 q, %0, %1;\n\t@q bar.arrive 9, 512;\n\t}" ::"r"(c.k), "n"(NIT - 1) : "memory");
        if (WTOP == 3) asm volatile("{\n\t.reg .pred q;\n\tsetp.ge.u32 q, %0, %1;\n\t@q nanosleep.u32 0;\n\t}" ::"r"(c.k), "n"(NIT - 1) : "memory");
        if (WTOP == 4) asm volatile("{\n\t.reg .pred q;\n\tsetp.ge.u32 q, %0, %1;\n\t@q st.volatile.shared.u32 [%2 + 120], %3;\n\t}" ::"r"(c.k), "n"(NIT - 1), "r"(c.bar), "r"(c.vz) : "memory");
        if (WTOP != 1) wgmma_wait<0>();
        TL(1 + c.k);
#undef par
    }
    {
        constexpr uint32_t par = (NIT - 1) & 1;
        uint32_t qa[12], qb[12], qh[12], hs[12], hk[12], v[12];
        constexpr int S0 = 12 - 12 * RANK, K0 = 12 * RANK;
        uint32_t pk[12];
        if (LWRAP(LA)) lock<1, 0, true>(c);
        if (LWRAP(LB)) lock<2, 0, true>(c);
        if (LWRAP(LC)) lock<3, 0, true>(c);
        phase1b<RANK, true>(c, accS, accK, accC, d0, d1, d2, u, qd, qh, hs, hk);
#define TE(n)
        TE(4);
        mma3(accS, qh, c, 0, 0, RANK == 0);
        if (EPI & 1) {
            sb(c);
            make_quads<0>(qa, d0, d2, u, 1);
            mma3(accS, qa, c, 0, 1, false);
            sb(c);
            make_quads<0>(qb, d0, d2, u, 2);
            mma3(accS, qb, c, 0, 2, false);
            wgmma_wait<3>();
            fence_regs(accK);
            mid_row<RANK, S0, S0 + 12>(accC, accK, hs, hk);
            send_half<0>(hs, c);
            send_half<1>(hs, c);
            send_half<2>(hs, c);
            sb(c);
        } else {
            wgmma_wait<1>();
            ld_chunk(d0, c, SL0, 1);
            ld_chunk(d0, c, SL0, 2);
            fence_regs(accK);
            mid_row<RANK, S0, S0 + 12>(accC, accK, hs, hk);
            send_half<0>(hs, c);
            send_half<1>(hs, c);
            send_half<2>(hs, c);
            sb(c);
            make_quads<0>(qa, d0, d2, u, 1);
            mma3(accS, qa, c, 0, 1, false);
            make_quads<0>(qb, d0, d2, u, 2);
            mma3(accS, qb, c, 0, 2, false);
        }
        TE(5);
        mid_row<RANK, K0, K0 + 12>(accC, accK, hs, hk);
        mbar_wait(c.bar + B_FULLB, par);
        TE(6);
        wgmma_wait<0>();
        TE(7);
        fence_regs(accS);
        mid_row<RANK, S0, S0 + 12>(accS, accK, hs, pk, 1.f);
        send_half<0, false>(hs, c);
        send_half<1, false>(hs, c);
        send_half<2, false>(hs, c);
        TE(8);
        mbar_wait(c.bar + B_HFULL, MRG & 1 ? 0 : par);
        TE(9);
        fin_load<3>(v, c, 2 * X_UNIT);
        mid_row<RANK, K0, K0 + 12>(accS, accK, hs, pk, 1.f);
        fin_store<3>(hk, v, c, 2 * X_UNIT, B_SH);
        mbar_wait(c.bar + B_FFULL + c.zero, par);
        TE(10);
        fin_load<3>(v, c, 0);
        fin_store<3>(pk, v, c, 0, B_SF);
        TL(17);
    }
}

__device__ __forceinline__ void wt_load(uint32_t (&g)[36], uint32_t unit, int lane) {
    const uint32_t src = unit + (lane >> 2) * 192 + ((lane & 3) << 4);
#pragma unroll
    for (int i = 0; i < 9; ++i)
        asm volatile("ld.shared.v4.b32 {%0, %1, %2, %3}, [%4];"
                     : "=r"(g[i * 4]), "=r"(g[i * 4 + 1]), "=r"(g[i * 4 + 2]), "=r"(g[i * 4 + 3])
                     : "r"(src + (i / 3) * 64 + (i % 3) * 2 * W_COMP) : "memory");
}
__device__ __forceinline__ void stsm(uint32_t addr, const uint32_t* v) {
    asm volatile("stmatrix.sync.aligned.m8n8.x4.shared.b16 [%0], {%1, %2, %3, %4};"
                 ::"r"(addr), "r"(v[0]), "r"(v[1]), "r"(v[2]), "r"(v[3]) : "memory");
}
template <int PART>
__device__ __forceinline__ void wt_store(const uint32_t (&g)[36], uint32_t unit, int lane) {
    const uint32_t dst = unit + (lane & 7) * 64 + ((((lane >> 3) ^ (lane >> 1)) & 3) << 4);
#pragma unroll
    for (int r = 0; r < 3; ++r) {
        const uint32_t *a = &g[r * 12], *b = a + 4, *cc = a + 8;
        uint32_t u1[4], u2[4], u3[4];
#pragma unroll
        for (int i = 0; i < 4; ++i) {
            uint32_t h;
            asm("add.rn.bf16x2 %0, %1, %2;" : "=r"(h) : "r"(a[i]), "r"(cc[i]));
            asm("mul.rn.bf16x2 %0, %1, %2;" : "=r"(h) : "r"(h), "r"(0x3f003f00u));
            asm("fma.rn.bf16x2 %0, %1, %2, %3;" : "=r"(u1[i]) : "r"(b[i]), "r"(0x3f003f00u), "r"(h));
            asm("fma.rn.bf16x2 %0, %1, %2, %3;" : "=r"(u2[i]) : "r"(b[i]), "r"(0xbf00bf00u), "r"(h));
            asm("mul.rn.bf16x2 %0, %1, %2;" : "=r"(h) : "r"(u2[i]), "r"(0xbaabbaabu));
            asm("fma.rn.bf16x2 %0, %0, %1, %2;" : "+r"(u2[i]) : "r"(0x3f2b3f2bu), "r"(h));
            asm("fma.rn.bf16x2 %0, %1, %2, %3;" : "=r"(h) : "r"(a[i]), "r"(0x3e803e80u), "r"(cc[i]));
            asm("fma.rn.bf16x2 %0, %1, %2, %3;" : "=r"(u3[i]) : "r"(h), "r"(0x40004000u), "r"(b[i]));
        }
        if (PART & 1) stsm(dst + r * 512 + CP(3) * W_COMP, u3);
        if (PART & 2) stsm(dst + r * 512 + CP(2) * W_COMP, u2);
        if (PART & 4) stsm(dst + r * 512 + CP(1) * W_COMP, u1);
        if (PART & 8) {
            stsm(dst + r * 512 + CP(0) * W_COMP, a);
            stsm(dst + r * 512 + CP(4) * W_COMP, cc);
        }
    }
}

__device__ __forceinline__ int seq_row(int seg, int row_par, int n) {
    const int q = (seg & 1) ? seg * SEG - 1 + n : seg * SEG + SEG - n;
    return 2 * q + row_par;
}

#define WF2 0
struct XMaps { CUtensorMap m[2]; };
#define xmap xm.m[0]
__global__ void __cluster_dims__(2, 1, 1) __launch_bounds__(384, 1)
conv_kernel(const char* __restrict__ wp, const char* __restrict__ xp,
            const __grid_constant__ XMaps xm, const __grid_constant__ CUtensorMap omap) {
    extern __shared__ uint8_t smem_raw[];
    const uint32_t base = (smem_u32(smem_raw) + 1023u) & ~1023u;
    const uint32_t wbase = base + OFF_W;
    const uint32_t bar_base = base + OFF_BAR;
    const uint32_t wbar_b = bar_base + 256, wready_b = bar_base + 280;

    const int tid = threadIdx.x;
    const int warp = tid >> 5, lane = tid & 31;
    const int rank = blockIdx.x & 1;
    const int cluster = blockIdx.x >> 1;
    const int strip = cluster & 7, seg = cluster >> 3;
    const int fmode = rank ? FMODE1 : FMODE0;
#define WPN 26
#define XPN 0
#define XPR 1
#define XPW 0
    uint32_t c_start;
    {
        const uint32_t t = tid - 96, l = blockIdx.x * 10 + t;
        asm volatile("{\n\t.reg .pred p;\n\tsetp.lt.u32 p, %1, %2;\n\t@p prefetch.global.L2 [%0];\n\t}" ::"l"(wp + l * 128), "r"(t), "n"(WPN) : "memory");
        if (XPN) {
            const uint32_t t2 = tid - 128;
            asm volatile("{\n\t.reg .pred p;\n\tsetp.lt.u32 p, %1, %2;\n\t@p prefetch.global.L2 [%0];\n\t}"
                         ::"l"(xp + (uint32_t)(seq_row(seg, XPW, XPR) * (IMG_W * 192) + (strip * 64 + rank * 32) * 192 + t2 * 128)), "r"(t2), "n"(XPN) : "memory");
        }
    }
    asm volatile("mov.u32 %0, %clock;" : "=r"(c_start) :: "memory");

#define SX(j)
    const int uwarp = __shfl_sync(0xffffffffu, warp, 0);
    const bool el = elect();
#define WPM 0
#define NOF 0
#define PFPOS 0
#define PFBLK
#define NPF 0
#define PFT 400
#define PFS 0
#define PORD 0xc4ab9231
#define PFL 48
    if (NPF && (unsigned)(tid - 128) < NPF * PFL) {
        const int i = (tid - 128) / PFL, e = (PORD >> (i * 4)) & 15;
        const int prow = seq_row(seg, e >> 3, e & 7);
        const char* p = xp + (size_t)prow * (IMG_W * 192) + (strip * 64 + rank * 32) * 192 + (tid - 128 - i * PFL) * 128;
        if (PFT) while ((uint32_t)clock() - c_start < PFT + (warp - 4) * PFS) {}
        asm volatile("prefetch.global.L2 [%0];" ::"l"(p) : "memory");
        if (warp == 4) SX(7);
    }
    if (uwarp == 0 && el) {
        for (int i = 0; i < 3; ++i) mbar_init(wbar_b + i * 8, 1);
        if (!(NOF & 1)) asm volatile("fence.proxy.async.shared::cta;" ::: "memory");
        else asm volatile("fence.mbarrier_init.release.cluster;" ::: "memory");
        const int up = (seg & 1) ^ 1;
        SX(2);
#pragma unroll
        for (int j = 0; j < 3; ++j) {
#pragma unroll
            for (int i = 0; i < 3; ++i)
                asm volatile("cp.async.bulk.shared::cluster.global.mbarrier::complete_tx::bytes [%0], [%1], %2, [%3];"
                             ::"r"(wbase + ((up ? 2 - i : i) * 6 + j) * W_TAP), "l"(wp + (2 * (i * 3 + j) + rank) * W_TAP),
                               "r"(W_TAP), "r"(wbar_b + j * 8) : "memory");
        }
        SX(3);
        for (int j = 0; j < 3; ++j) mbar_expect_tx(wbar_b + j * 8, 3 * W_TAP);
        asm volatile("fence.mbarrier_init.release.cluster;" ::: "memory");
    }
    if (PFPOS == 1) { PFBLK }
#define RT 320
    if (uwarp == 2 && el) {
        for (int i = 0; i < 2; ++i) {
            mbar_init(bar_base + i * 128 + B_FULLA, 3);
            mbar_init(bar_base + i * 128 + B_FULLB, 2);
            mbar_init(bar_base + i * 128 + B_EMPTYE, 4);
            mbar_init(bar_base + i * 128 + B_EMPTYF, 4);
            mbar_init(bar_base + i * 128 + B_EMPTYB, 4);
            mbar_init(bar_base + i * 128 + B_HFULL, 1);
            mbar_init(bar_base + i * 128 + B_FFULL, 1);
            mbar_init(bar_base + i * 128 + B_SH, 4);
            mbar_init(bar_base + i * 128 + B_SF, 4);
            mbar_expect_tx(bar_base + i * 128 + B_HFULL, X_TX);
            mbar_expect_tx(bar_base + i * 128 + B_FFULL, 2 * X_TX);
            if (!WFA) mbar_arrive(bar_base + i * 128 + B_FULLA);
        }
        mbar_init(wready_b, 10);
        mbar_init(wready_b + 8, 4);
        mbar_init(wready_b + 16, WF2 ? 4 : 1);
        mbar_init(wready_b + 24, 4);
        mbar_init(wready_b + 32, 1);
        asm volatile("fence.mbarrier_init.release.cluster;" ::: "memory");
        asm volatile("fence.proxy.async.shared::cta;" ::: "memory");
    }
    if (uwarp == 10 && el) {
        asm volatile("prefetch.tensormap [%0];" ::"l"((uint64_t)(&xmap)) : "memory");
        asm volatile("prefetch.tensormap [%0];" ::"l"((uint64_t)(&xmap + 1)) : "memory");
        for (int i = 0; i < 4; ++i) mbar_init(bar_base + (i >> 1) * 128 + (i & 1) * B_FULLC, 1);
        for (int i = 0; i < 4; ++i) mbar_expect_tx(bar_base + (i >> 1) * 128 + (i & 1) * B_FULLC, (2 - (i & 1)) * IN_ROW);
        asm volatile("fence.mbarrier_init.release.cluster;" ::: "memory");
        if (!(NOF & 2)) asm volatile("fence.proxy.async.shared::cta;" ::: "memory");
    }
    __syncwarp();
    asm volatile("barrier.cluster.arrive.relaxed.aligned;" ::: "memory");
#define RSTEP 150
    if (uwarp == 10 && el) {
#pragma unroll
        for (int i = 0; i < 6; ++i) {
            const int wg = (RORD >> (i * 4 + 2)) & 1, n = (RORD >> (i * 4)) & 3;
            const uint32_t fb = bar_base + wg * 128 + (n == 2 ? B_FULLC : B_FULL0);
            if (i == 0 || RSTEP) while ((uint32_t)clock() - c_start < ROW_DELAY + i * RSTEP) {}
            const uint32_t dst = base + (n == 1 ? OFF_X + wg * X_BYTES : OFF_IN + wg * 4 * IN_ROW + n * 2 * IN_SLAB);
            load_row(dst, dst + (n == 1 ? 2 * IN_SLAB : IN_B - n * IN_SLAB), &xmap, fb, rank, strip, seq_row(seg, wg, n), true);
            if (i < 2) SX(4 + i);
            if (i == 5) SX(6);
        }
    }
    __syncwarp();
#define ST(j)
    ST(0);
    asm volatile("barrier.cluster.wait.aligned;" ::: "memory");
#define RLW 1
#define WX 4
#define HW0 11
#define HW1 9
#define P1M 1
#define P2M 6
#define WF1 0
    if (uwarp < 4 || uwarp == HW0 || uwarp == HW1) {
        uint32_t ga[36];
        const int uw = uwarp < 4 ? uwarp : uwarp == HW0 ? 4 : 5;
        const uint32_t unit = wbase + uw * W_K8;
        ST(1);
        mbar_wait(wbar_b, 0);
        ST(2);
        wt_load(ga, unit, lane);
        __syncwarp();
        wt_store<15>(ga, unit, lane);
        ST(5);
        if (WF1) asm volatile("fence.proxy.async.shared::cta;" ::: "memory");
        mbar_arrive_warp(wready_b);
        ST(6);
    } else if (uwarp < 8) {
        uint32_t ga[36], gb[36], gc[36];
        const uint32_t unit = wbase + (uwarp + 2) * W_K8;
        ST(1);
        mbar_wait(wbar_b + 8, 0);
        wt_load(ga, unit, lane);
        mbar_wait(wbar_b + (uwarp < 6 ? 8 : 16), 0);
        wt_load(gb, unit + 4 * W_K8, lane);
        mbar_wait(wbar_b + 16, 0);
        ST(2);
        wt_load(gc, unit + 8 * W_K8, lane);
        __syncwarp();
        wt_store<P1M>(ga, unit, lane);
        wt_store<P1M>(gb, unit + 4 * W_K8, lane);
        wt_store<P1M>(gc, unit + 8 * W_K8, lane);
        if (WF1) asm volatile("fence.proxy.async.shared::cta;" ::: "memory");
        mbar_arrive_warp(wready_b);
        ST(3);
        if (P2M) {
            wt_store<P2M>(ga, unit, lane);
            wt_store<P2M>(gb, unit + 4 * W_K8, lane);
            wt_store<P2M>(gc, unit + 8 * W_K8, lane);
            mbar_arrive_warp(wready_b + 24);
        }
        ST(4);
        wt_store<15 - P1M - P2M>(ga, unit, lane);
        wt_store<15 - P1M - P2M>(gb, unit + 4 * W_K8, lane);
        wt_store<15 - P1M - P2M>(gc, unit + 8 * W_K8, lane);
        ST(5);
        if (WF2) asm volatile("fence.proxy.async.shared::cta;" ::: "memory");
        mbar_arrive_warp(wready_b + (WF2 ? 16 : 8));
        ST(6);
    }

    if (uwarp >= 8) {
        asm volatile("setmaxnreg.dec.sync.aligned.u32 24;");
        {
            const int wg = uwarp & 1;
            const uint32_t bar = bar_base + wg * 128;
            const int step = (seg & 1) ? 2 : -2;
            if (uwarp < 10) {
                const uint32_t in = base + OFF_IN + wg * 4 * IN_ROW;
                const char* pf = xp + (strip * 64 + rank * 32) * 192;
                int row = seq_row(seg, wg, 0);
#pragma unroll 1
                for (int t = 0; t < NIT; ++t, row += 3 * step) {
#pragma unroll
                    for (int g = 0; g < 3; ++g) {
                        const int sl = g == 2 ? 2 : (g ^ rank ^ 1);
                        const uint32_t fb = bar + (g == 2 ? B_FULLB : B_FULLA);
                        if (g == 1 && (MRG & 2)) mbar_wait_h(bar + B_SH, ~t & 1);
                        else mbar_wait_h(bar + B_EMPTYE + g * 8, t & 1);
                        STAMP(t, 6 + g);
                        if (el) {
                            const bool ld = t < NIT - 1 || sl == 0;
                            if (ld) {
                                if (g == 2) load_row(in + 2 * SL3, in + IN_B + SL3, &xmap, fb, rank, strip, row + 6 * step, true);
                                load_row(in + sl * 2 * IN_SLAB, in + IN_B + sl * IN_SLAB, &xmap, fb, rank, strip, row + (g == 2 ? 5 : 4 * sl) * step, true);
                            }
                            mbar_expect_tx(fb, ld ? (g == 2 ? 2 * IN_ROW + (MRG & 1) * X_TX : IN_ROW) : 0);
                            if (g == 2 && t == 0) mbar_arrive_remote(mapa(fb, rank ^ 1));
                            const int n = 3 * t + g + 1, prow = row + (g + 1 + PF) * step;
                            if (n >= PF0 && n + PF < SEG + 2 && (unsigned)prow < IMG_H)
                                asm volatile("cp.async.bulk.prefetch.L2.global [%0], %1;"
                                             ::"l"(pf + (size_t)prow * (IMG_W * 192)), "r"(32 * 192) : "memory");
#define EPT 0
                            if (EPT && n < 5) {
                                const int e0 = (EPT >> (n * 8 - 8)) & 15, e1 = (EPT >> (n * 8 - 4)) & 15;
                                if (e0) asm volatile("cp.async.bulk.prefetch.L2.global [%0], %1;"
                                                     ::"l"(pf + (size_t)(row + (e0 - 3 * t) * step) * (IMG_W * 192)), "r"(32 * 192) : "memory");
                                if (e1) asm volatile("cp.async.bulk.prefetch.L2.global [%0], %1;"
                                                     ::"l"(pf + (size_t)(row + (e1 - 3 * t) * step) * (IMG_W * 192)), "r"(32 * 192) : "memory");
                            }
                        }
                        __syncwarp();
                        if (g) STAMP(t, 8 + g);
                    }
                }
            } else {
                const uint32_t src = base + OFF_X + wg * X_BYTES;
                const uint32_t r_bar = mapa(bar, rank ^ 1);
                if (wg == 0 && lane < 4)
                    asm volatile("mbarrier.arrive.shared::cta.b64 _, [%0], 4;" ::"r"(bar + (lane >> 1) * 128 + B_EMPTYE + (lane & 1) * 8) : "memory");
                __syncwarp();
                if (wg == RLW) {
                    if (P2M) {
                        mbar_wait(wready_b + 24, 0);
                        asm volatile("fence.proxy.async.shared::cta;" ::: "memory");
                        mbar_arrive_warp(wready_b + 32);
                    }
                    if (!WF2) {
                        mbar_wait(wready_b + 8, 0);
                        asm volatile("fence.proxy.async.shared::cta;" ::: "memory");
                        if (WFA) { if (lane < 2) mbar_arrive(bar_base + lane * 128 + B_FULLA); }
                        else mbar_arrive_warp(wready_b + 16);
                    }
                    if (RLW) ST(7);
                }
                int row = seq_row(seg, wg, 1);
#pragma unroll 1
                for (int t = 0; t < NIT; ++t, row += 3 * step) {
                    const bool last = t == NIT - 1;
                    mbar_wait_h(bar + B_SH, t & 1);
                    STAMP(t, 0);
                    if (el) {
                        asm volatile("fence.proxy.async.shared::cta;" ::: "memory");
                        tma_store_4d(&omap, src + 2 * X_UNIT, 0, strip * 16, rank, row + step, EF(t, 2));
                        asm volatile("cp.async.bulk.commit_group;" ::: "memory");
                        if (!last) {
                            if (!(MRG & 1)) mbar_expect_tx(bar + B_HFULL, X_TX);
                            asm volatile("cp.async.bulk.wait_group.read 0;" ::: "memory");
                            mbar_arrive_remote(r_bar + B_FULLA);
                        }
                    }
                    __syncwarp();
                    STAMP(t, 1);
                    mbar_wait_h(bar + B_SF, t & 1);
                    STAMP(t, 2);
                    if (el) {
                        asm volatile("fence.proxy.async.shared::cta;" ::: "memory");
                        const int orow = row + (last ? 0 : 2 * rank * step);
                        tma_store_4d(&omap, src, 0, strip * 16, last ? rank : 0, orow, EF(t, 0));
                        if (!last) tma_store_4d(&omap, src + X_UNIT, 0, strip * 16, 1, orow, EF(t, 1));
                        asm volatile("cp.async.bulk.commit_group;" ::: "memory");
                        if (!last) mbar_expect_tx(bar + B_FFULL, t == NIT - 2 ? X_TX : 2 * X_TX);
                        asm volatile("cp.async.bulk.wait_group.read 0;" ::: "memory");
                        if (!last) mbar_arrive_remote(r_bar + B_FULLB);
                    }
                    __syncwarp();
                    STAMP(t, 3);
                }
            }
        }
    } else {
        const int wg = uwarp >> 2;
        const int w4 = warp & 3;
        if (RT >= 256) asm volatile("setmaxnreg.inc.sync.aligned.u32 240;");
        ST(7);
        Ctx c;
        c.bar = bar_base + wg * 128;
        c.wdesc = ((wbase & 0x3FFFF) >> 4) | ((uint32_t)(512 >> 4) << 16);
        c.wready = wready_b;
        c.wg = wg;
        c.k = ~0u;
        c.zero = 0;
        c.tlo2 = bar_base + 576 - bar_base * 4;
        c.tlo = 320;
        {
            const int m = lane >> 3, gg = lane & 7, hl = m >> 1;
            const int rho0 = (m & 1) ? (8 * w4 + gg + 2) : (36 + 8 * w4 + gg);
            const int rho1 = rho0 + 2;
            const uint32_t in = base + OFF_IN + wg * 4 * IN_ROW;
            c.ld0 = in + IN_B + rho0 * 32 + ((hl ^ ((rho0 >> 2) & 1)) << 4);
            c.ld1 = in + IN_B + rho1 * 32 + ((hl ^ ((rho1 >> 2) & 1)) << 4);
            c.vz = (rho0 & 2) << 3;
            c.ua = in - 2 * (in + IN_B);
        }
        c.xbuf = base + OFF_X + wg * X_BYTES + (tid & 127) * 16;
        c.r_off = mapa(c.bar, rank ^ 1) - c.bar;
        c.ld0 = __shfl_sync(0xffffffffu, c.ld0, lane);
        c.ld1 = __shfl_sync(0xffffffffu, c.ld1, lane);
        c.xbuf = __shfl_sync(0xffffffffu, c.xbuf, lane);
        TL(1);
        TLC(20);
        if (rank == 0) consumer<0>(c);
        else consumer<1>(c);
        TLC(21);
    }
}

typedef CUresult (*EncodeFn)(CUtensorMap*, CUtensorMapDataType, cuuint32_t, void*, const cuuint64_t*,
                             const cuuint64_t*, const cuuint32_t*, const cuuint32_t*, CUtensorMapInterleave,
                             CUtensorMapSwizzle, CUtensorMapL2promotion, CUtensorMapFloatOOBfill);

}

extern "C" void kernel_launch(void* const* d_in, const int* in_sizes, int n_in, void* d_out, int out_size) {
    (void)in_sizes; (void)n_in; (void)out_size;
    static EncodeFn encode = nullptr;
    if (!encode) {
        void* fn = nullptr;
        cudaDriverEntryPointQueryResult qres;
        cudaGetDriverEntryPoint("cuTensorMapEncodeTiled", &fn, cudaEnableDefault, &qres);
        encode = (EncodeFn)fn;
        cudaFuncSetAttribute(conv_kernel, cudaFuncAttributeMaxDynamicSharedMemorySize, SMEM_BYTES);
    }
    XMaps xm;
    CUtensorMap omap;
    cuuint32_t estr5[5] = {1, 1, 1, 1, 1};
    {
        cuuint64_t dims[5] = {(cuuint64_t)CH, 2, (cuuint64_t)IMG_W / 4, 2, (cuuint64_t)IMG_H};
        cuuint64_t strides[4] = {(cuuint64_t)CH * 2, (cuuint64_t)CH * 2 * 4, (cuuint64_t)CH * 2 * 2,
                                 (cuuint64_t)IMG_W * CH * 2};
        cuuint32_t box[5] = {16, 2, 18, 2, 1};
        encode(&xmap, CU_TENSOR_MAP_DATA_TYPE_BFLOAT16, 5, d_in[0], dims, strides, box, estr5,
               CU_TENSOR_MAP_INTERLEAVE_NONE, CU_TENSOR_MAP_SWIZZLE_32B, PROMO,
               CU_TENSOR_MAP_FLOAT_OOB_FILL_NONE);
        box[0] = 32;
        encode(&xm.m[1], CU_TENSOR_MAP_DATA_TYPE_BFLOAT16, 5, d_in[0], dims, strides, box, estr5,
               CU_TENSOR_MAP_INTERLEAVE_NONE, CU_TENSOR_MAP_SWIZZLE_64B, PROMO,
               CU_TENSOR_MAP_FLOAT_OOB_FILL_NONE);
    }
    {
        cuuint64_t dims[5] = {32, 2, (cuuint64_t)IMG_H * IMG_W / 4, 3, 2};
        cuuint64_t strides[4] = {(cuuint64_t)CH * 2, (cuuint64_t)CH * 2 * 4, 64, (cuuint64_t)CH * 2 * 2};
        cuuint32_t box[5] = {32, 2, 16, 3, 1};
        encode(&omap, CU_TENSOR_MAP_DATA_TYPE_BFLOAT16, 5, d_out, dims, strides, box, estr5,
               CU_TENSOR_MAP_INTERLEAVE_NONE, CU_TENSOR_MAP_SWIZZLE_NONE, CU_TENSOR_MAP_L2_PROMOTION_NONE,
               CU_TENSOR_MAP_FLOAT_OOB_FILL_NONE);
    }
    conv_kernel<<<NUM_CTAS, 384, SMEM_BYTES>>>((const char*)d_in[1], (const char*)d_in[0], xm, omap);
}
```
